```python
import torch

def _softmax(x, axis=-1):
    return torch.softmax(x, dim=axis)
def _gelu(x):
    return torch.nn.functional.gelu(x, approximate="tanh")
def _silu(x):
    return torch.nn.functional.silu(x)
def _sigmoid(x):
    return torch.sigmoid(x)
def _layernorm(x, axis=-1, eps=1e-5):
    m = x.mean(dim=axis, keepdim=True)
    v = x.var(dim=axis, keepdim=True, unbiased=False)
    return (x - m) / torch.sqrt(v + eps)
def _scatter_add(tgt, idx, src, axis=0):
    return tgt.clone().index_add_(axis, idx, src)
def _segment_sum(src, seg, n):
    out = torch.zeros((n,) + src.shape[1:], dtype=src.dtype)
    return out.index_add_(0, seg, src)
def _pad(x, pw):
    flat = tuple(v for pair in reversed(pw) for v in pair)
    return torch.nn.functional.pad(x, flat)

kernel_name = 'sequential_preLN__ssm_conv_h3__glu_gated_swiglu__prompt'

def setup_inputs():

    _w = (lambda a: (lambda t: t.to(torch.bfloat16) if t.is_floating_point() else t)(torch.as_tensor(a)))
    def _A_setup():
        B, S, D = 1, 2048, 640
        ks = 4
        return {
            "q": _w((lambda *s: torch.randn(*s, dtype=torch.bfloat16) * 0.05)(B, S, D)),
            "k": _w((lambda *s: torch.randn(*s, dtype=torch.bfloat16) * 0.2)(B, S, D)),
            "v": _w((lambda *s: torch.randn(*s, dtype=torch.bfloat16) * 0.2)(B, S, D)),
            "shift_k": _w((lambda *s: torch.randn(*s, dtype=torch.bfloat16) * 0.2)(D, ks) * 0.5),
            "ssm_k": _w((lambda *s: torch.randn(*s, dtype=torch.bfloat16) * 0.4)(D, S) * (1.0 / S ** 0.5)),
            "ssm_D": _w((lambda *s: torch.randn(*s, dtype=torch.bfloat16) * 0.2)(D)),
        }
    _A_in = _A_setup()

    def _B_setup():
        B, S, D, F = 1, 2048, 640, 1536
        return {
            "x": _w((lambda *s: torch.randn(*s, dtype=torch.bfloat16) * 0.05)(B, S, D)),
            "w1": _w((lambda *s: torch.randn(*s, dtype=torch.bfloat16) * 0.2)(D, F) * (2.0 / D) ** 0.5),
            "w3": _w((lambda *s: torch.randn(*s, dtype=torch.bfloat16) * 0.2)(D, F) * (2.0 / D) ** 0.5),
            "w2": _w((lambda *s: torch.randn(*s, dtype=torch.bfloat16) * 0.2)(F, D) * (2.0 / F) ** 0.5),
        }
    _B_in = _B_setup()

    return {
        "A_q": _A_in["q"],
        "A_k": _A_in["k"],
        "A_v": _A_in["v"],
        "A_shift_k": _A_in["shift_k"],
        "A_ssm_k": _A_in["ssm_k"],
        "A_ssm_D": _A_in["ssm_D"],
        "B_x": _B_in["x"],
        "B_w1": _B_in["w1"],
        "B_w3": _B_in["w3"],
        "B_w2": _B_in["w2"],
    }

def reference(A_q, A_k, A_v, A_shift_k, A_ssm_k, A_ssm_D, B_x, B_w1, B_w3, B_w2):
    def _A_ref(q, k, v, shift_k, ssm_k, ssm_D):
        B, S, D = q.shape
        ks = shift_k.shape[-1]
        k_pad = _pad(k, ((0, 0), (ks - 1, 0), (0, 0)))
        k_shift = torch.zeros_like(k)
        for t in range(ks):
            k_shift = k_shift + k_pad[:, t:t + S, :] * shift_k[:, ks - 1 - t][None, None, :]
        kv = k_shift * v
        L = 2 * S
        kv_pad = _pad(kv, ((0, 0), (0, S), (0, 0)))
        kf_pad = _pad(ssm_k, ((0, 0), (0, S)))
        kv_f = (lambda x, axes=(-2,-1): torch.fft.rfft2(x.float(), dim=axes))(kv_pad[:, None, :, :], axes=(1, 2))
        kf_f = (lambda x, axes=(-2,-1): torch.fft.rfft2(x.float(), dim=axes))(kf_pad[:, None, :], axes=(1, 2))
        kf_f = (lambda x, *d: x.permute(*d))(kf_f, 1, 2, 0)
        y_f = kv_f * kf_f[None, :, :, :]
        y = (lambda x, s, axes=(-2,-1): torch.fft.irfft2(x, s=s, dim=axes).to(torch.bfloat16))(y_f, (1, L), axes=(1, 2))[:, 0, :S, :]
        y = y + kv * ssm_D[None, None, :]
        return q * y

    def _B_ref(x, w1, w3, w2):
        gate = torch.einsum("bsd,df->bsf", x, w1)
        up = torch.einsum("bsd,df->bsf", x, w3)
        h = _silu(gate) * up
        out = torch.einsum("bsf,fd->bsd", h, w2)
        return out

    x = A_q
    h = x + _A_ref(_layernorm(x, axis=-1), A_k, A_v, A_shift_k, A_ssm_k, A_ssm_D)
    h2 = h + _B_ref(_layernorm(h, axis=-1), B_w1, B_w3, B_w2)
    return h2
```

```cpp
#include <cuda_runtime.h>
#include <cuda_bf16.h>
#include <cuda.h>
#include <stdint.h>

typedef __nv_bfloat16 bf16;
constexpr int S_ = 2048, D_ = 640;

template<int N, int ACC> __device__ __forceinline__ void wgmma_rs(float* d, const uint32_t* a, uint64_t db);
template<int TA, int TB, int ACC> __device__ __forceinline__ void wgmma_ss(float* d, uint64_t da, uint64_t db);
template<> __device__ __forceinline__ void wgmma_rs<128, 0>(float* d, const uint32_t* a, uint64_t db) {
  asm volatile("{\n.reg .pred p;\nsetp.ne.b32 p, 0, 0;\n"
    "wgmma.mma_async.sync.aligned.m64n128k16.f32.bf16.bf16 {%0, %1, %2, %3, %4, %5, %6, %7, %8, %9, %10, %11, %12, %13, %14, %15, %16, %17, %18, %19, %20, %21, %22, %23, %24, %25, %26, %27, %28, %29, %30, %31, %32, %33, %34, %35, %36, %37, %38, %39, %40, %41, %42, %43, %44, %45, %46, %47, %48, %49, %50, %51, %52, %53, %54, %55, %56, %57, %58, %59, %60, %61, %62, %63}, {%64, %65, %66, %67}, %68, p, 1, 1, 0;\n}\n"
    : "=f"(d[0]), "=f"(d[1]), "=f"(d[2]), "=f"(d[3]), "=f"(d[4]), "=f"(d[5]), "=f"(d[6]), "=f"(d[7]), "=f"(d[8]), "=f"(d[9]), "=f"(d[10]), "=f"(d[11]), "=f"(d[12]), "=f"(d[13]), "=f"(d[14]), "=f"(d[15]), "=f"(d[16]), "=f"(d[17]), "=f"(d[18]), "=f"(d[19]), "=f"(d[20]), "=f"(d[21]), "=f"(d[22]), "=f"(d[23]), "=f"(d[24]), "=f"(d[25]), "=f"(d[26]), "=f"(d[27]), "=f"(d[28]), "=f"(d[29]), "=f"(d[30]), "=f"(d[31]), "=f"(d[32]), "=f"(d[33]), "=f"(d[34]), "=f"(d[35]), "=f"(d[36]), "=f"(d[37]), "=f"(d[38]), "=f"(d[39]), "=f"(d[40]), "=f"(d[41]), "=f"(d[42]), "=f"(d[43]), "=f"(d[44]), "=f"(d[45]), "=f"(d[46]), "=f"(d[47]), "=f"(d[48]), "=f"(d[49]), "=f"(d[50]), "=f"(d[51]), "=f"(d[52]), "=f"(d[53]), "=f"(d[54]), "=f"(d[55]), "=f"(d[56]), "=f"(d[57]), "=f"(d[58]), "=f"(d[59]), "=f"(d[60]), "=f"(d[61]), "=f"(d[62]), "=f"(d[63]) : "r"(a[0]), "r"(a[1]), "r"(a[2]), "r"(a[3]), "l"(db));
}
template<> __device__ __forceinline__ void wgmma_rs<16, 1>(float* d, const uint32_t* a, uint64_t db) {
  asm volatile("{\n.reg .pred p;\nsetp.ne.b32 p, 1, 0;\n"
    "wgmma.mma_async.sync.aligned.m64n16k16.f32.bf16.bf16 {%0, %1, %2, %3, %4, %5, %6, %7}, {%8, %9, %10, %11}, %12, p, 1, 1, 0;\n}\n"
    : "+f"(d[0]), "+f"(d[1]), "+f"(d[2]), "+f"(d[3]), "+f"(d[4]), "+f"(d[5]), "+f"(d[6]), "+f"(d[7]) : "r"(a[0]), "r"(a[1]), "r"(a[2]), "r"(a[3]), "l"(db));
}
template<> __device__ __forceinline__ void wgmma_rs<32, 1>(float* d, const uint32_t* a, uint64_t db) {
  asm volatile("{\n.reg .pred p;\nsetp.ne.b32 p, 1, 0;\n"
    "wgmma.mma_async.sync.aligned.m64n32k16.f32.bf16.bf16 {%0, %1, %2, %3, %4, %5, %6, %7, %8, %9, %10, %11, %12, %13, %14, %15}, {%16, %17, %18, %19}, %20, p, 1, 1, 0;\n}\n"
    : "+f"(d[0]), "+f"(d[1]), "+f"(d[2]), "+f"(d[3]), "+f"(d[4]), "+f"(d[5]), "+f"(d[6]), "+f"(d[7]), "+f"(d[8]), "+f"(d[9]), "+f"(d[10]), "+f"(d[11]), "+f"(d[12]), "+f"(d[13]), "+f"(d[14]), "+f"(d[15]) : "r"(a[0]), "r"(a[1]), "r"(a[2]), "r"(a[3]), "l"(db));
}
template<> __device__ __forceinline__ void wgmma_rs<48, 1>(float* d, const uint32_t* a, uint64_t db) {
  asm volatile("{\n.reg .pred p;\nsetp.ne.b32 p, 1, 0;\n"
    "wgmma.mma_async.sync.aligned.m64n48k16.f32.bf16.bf16 {%0, %1, %2, %3, %4, %5, %6, %7, %8, %9, %10, %11, %12, %13, %14, %15, %16, %17, %18, %19, %20, %21, %22, %23}, {%24, %25, %26, %27}, %28, p, 1, 1, 0;\n}\n"
    : "+f"(d[0]), "+f"(d[1]), "+f"(d[2]), "+f"(d[3]), "+f"(d[4]), "+f"(d[5]), "+f"(d[6]), "+f"(d[7]), "+f"(d[8]), "+f"(d[9]), "+f"(d[10]), "+f"(d[11]), "+f"(d[12]), "+f"(d[13]), "+f"(d[14]), "+f"(d[15]), "+f"(d[16]), "+f"(d[17]), "+f"(d[18]), "+f"(d[19]), "+f"(d[20]), "+f"(d[21]), "+f"(d[22]), "+f"(d[23]) : "r"(a[0]), "r"(a[1]), "r"(a[2]), "r"(a[3]), "l"(db));
}
template<> __device__ __forceinline__ void wgmma_rs<64, 1>(float* d, const uint32_t* a, uint64_t db) {
  asm volatile("{\n.reg .pred p;\nsetp.ne.b32 p, 1, 0;\n"
    "wgmma.mma_async.sync.aligned.m64n64k16.f32.bf16.bf16 {%0, %1, %2, %3, %4, %5, %6, %7, %8, %9, %10, %11, %12, %13, %14, %15, %16, %17, %18, %19, %20, %21, %22, %23, %24, %25, %26, %27, %28, %29, %30, %31}, {%32, %33, %34, %35}, %36, p, 1, 1, 0;\n}\n"
    : "+f"(d[0]), "+f"(d[1]), "+f"(d[2]), "+f"(d[3]), "+f"(d[4]), "+f"(d[5]), "+f"(d[6]), "+f"(d[7]), "+f"(d[8]), "+f"(d[9]), "+f"(d[10]), "+f"(d[11]), "+f"(d[12]), "+f"(d[13]), "+f"(d[14]), "+f"(d[15]), "+f"(d[16]), "+f"(d[17]), "+f"(d[18]), "+f"(d[19]), "+f"(d[20]), "+f"(d[21]), "+f"(d[22]), "+f"(d[23]), "+f"(d[24]), "+f"(d[25]), "+f"(d[26]), "+f"(d[27]), "+f"(d[28]), "+f"(d[29]), "+f"(d[30]), "+f"(d[31]) : "r"(a[0]), "r"(a[1]), "r"(a[2]), "r"(a[3]), "l"(db));
}
template<> __device__ __forceinline__ void wgmma_rs<80, 1>(float* d, const uint32_t* a, uint64_t db) {
  asm volatile("{\n.reg .pred p;\nsetp.ne.b32 p, 1, 0;\n"
    "wgmma.mma_async.sync.aligned.m64n80k16.f32.bf16.bf16 {%0, %1, %2, %3, %4, %5, %6, %7, %8, %9, %10, %11, %12, %13, %14, %15, %16, %17, %18, %19, %20, %21, %22, %23, %24, %25, %26, %27, %28, %29, %30, %31, %32, %33, %34, %35, %36, %37, %38, %39}, {%40, %41, %42, %43}, %44, p, 1, 1, 0;\n}\n"
    : "+f"(d[0]), "+f"(d[1]), "+f"(d[2]), "+f"(d[3]), "+f"(d[4]), "+f"(d[5]), "+f"(d[6]), "+f"(d[7]), "+f"(d[8]), "+f"(d[9]), "+f"(d[10]), "+f"(d[11]), "+f"(d[12]), "+f"(d[13]), "+f"(d[14]), "+f"(d[15]), "+f"(d[16]), "+f"(d[17]), "+f"(d[18]), "+f"(d[19]), "+f"(d[20]), "+f"(d[21]), "+f"(d[22]), "+f"(d[23]), "+f"(d[24]), "+f"(d[25]), "+f"(d[26]), "+f"(d[27]), "+f"(d[28]), "+f"(d[29]), "+f"(d[30]), "+f"(d[31]), "+f"(d[32]), "+f"(d[33]), "+f"(d[34]), "+f"(d[35]), "+f"(d[36]), "+f"(d[37]), "+f"(d[38]), "+f"(d[39]) : "r"(a[0]), "r"(a[1]), "r"(a[2]), "r"(a[3]), "l"(db));
}
template<> __device__ __forceinline__ void wgmma_rs<96, 1>(float* d, const uint32_t* a, uint64_t db) {
  asm volatile("{\n.reg .pred p;\nsetp.ne.b32 p, 1, 0;\n"
    "wgmma.mma_async.sync.aligned.m64n96k16.f32.bf16.bf16 {%0, %1, %2, %3, %4, %5, %6, %7, %8, %9, %10, %11, %12, %13, %14, %15, %16, %17, %18, %19, %20, %21, %22, %23, %24, %25, %26, %27, %28, %29, %30, %31, %32, %33, %34, %35, %36, %37, %38, %39, %40, %41, %42, %43, %44, %45, %46, %47}, {%48, %49, %50, %51}, %52, p, 1, 1, 0;\n}\n"
    : "+f"(d[0]), "+f"(d[1]), "+f"(d[2]), "+f"(d[3]), "+f"(d[4]), "+f"(d[5]), "+f"(d[6]), "+f"(d[7]), "+f"(d[8]), "+f"(d[9]), "+f"(d[10]), "+f"(d[11]), "+f"(d[12]), "+f"(d[13]), "+f"(d[14]), "+f"(d[15]), "+f"(d[16]), "+f"(d[17]), "+f"(d[18]), "+f"(d[19]), "+f"(d[20]), "+f"(d[21]), "+f"(d[22]), "+f"(d[23]), "+f"(d[24]), "+f"(d[25]), "+f"(d[26]), "+f"(d[27]), "+f"(d[28]), "+f"(d[29]), "+f"(d[30]), "+f"(d[31]), "+f"(d[32]), "+f"(d[33]), "+f"(d[34]), "+f"(d[35]), "+f"(d[36]), "+f"(d[37]), "+f"(d[38]), "+f"(d[39]), "+f"(d[40]), "+f"(d[41]), "+f"(d[42]), "+f"(d[43]), "+f"(d[44]), "+f"(d[45]), "+f"(d[46]), "+f"(d[47]) : "r"(a[0]), "r"(a[1]), "r"(a[2]), "r"(a[3]), "l"(db));
}
template<> __device__ __forceinline__ void wgmma_rs<112, 1>(float* d, const uint32_t* a, uint64_t db) {
  asm volatile("{\n.reg .pred p;\nsetp.ne.b32 p, 1, 0;\n"
    "wgmma.mma_async.sync.aligned.m64n112k16.f32.bf16.bf16 {%0, %1, %2, %3, %4, %5, %6, %7, %8, %9, %10, %11, %12, %13, %14, %15, %16, %17, %18, %19, %20, %21, %22, %23, %24, %25, %26, %27, %28, %29, %30, %31, %32, %33, %34, %35, %36, %37, %38, %39, %40, %41, %42, %43, %44, %45, %46, %47, %48, %49, %50, %51, %52, %53, %54, %55}, {%56, %57, %58, %59}, %60, p, 1, 1, 0;\n}\n"
    : "+f"(d[0]), "+f"(d[1]), "+f"(d[2]), "+f"(d[3]), "+f"(d[4]), "+f"(d[5]), "+f"(d[6]), "+f"(d[7]), "+f"(d[8]), "+f"(d[9]), "+f"(d[10]), "+f"(d[11]), "+f"(d[12]), "+f"(d[13]), "+f"(d[14]), "+f"(d[15]), "+f"(d[16]), "+f"(d[17]), "+f"(d[18]), "+f"(d[19]), "+f"(d[20]), "+f"(d[21]), "+f"(d[22]), "+f"(d[23]), "+f"(d[24]), "+f"(d[25]), "+f"(d[26]), "+f"(d[27]), "+f"(d[28]), "+f"(d[29]), "+f"(d[30]), "+f"(d[31]), "+f"(d[32]), "+f"(d[33]), "+f"(d[34]), "+f"(d[35]), "+f"(d[36]), "+f"(d[37]), "+f"(d[38]), "+f"(d[39]), "+f"(d[40]), "+f"(d[41]), "+f"(d[42]), "+f"(d[43]), "+f"(d[44]), "+f"(d[45]), "+f"(d[46]), "+f"(d[47]), "+f"(d[48]), "+f"(d[49]), "+f"(d[50]), "+f"(d[51]), "+f"(d[52]), "+f"(d[53]), "+f"(d[54]), "+f"(d[55]) : "r"(a[0]), "r"(a[1]), "r"(a[2]), "r"(a[3]), "l"(db));
}
template<> __device__ __forceinline__ void wgmma_rs<128, 1>(float* d, const uint32_t* a, uint64_t db) {
  asm volatile("{\n.reg .pred p;\nsetp.ne.b32 p, 1, 0;\n"
    "wgmma.mma_async.sync.aligned.m64n128k16.f32.bf16.bf16 {%0, %1, %2, %3, %4, %5, %6, %7, %8, %9, %10, %11, %12, %13, %14, %15, %16, %17, %18, %19, %20, %21, %22, %23, %24, %25, %26, %27, %28, %29, %30, %31, %32, %33, %34, %35, %36, %37, %38, %39, %40, %41, %42, %43, %44, %45, %46, %47, %48, %49, %50, %51, %52, %53, %54, %55, %56, %57, %58, %59, %60, %61, %62, %63}, {%64, %65, %66, %67}, %68, p, 1, 1, 0;\n}\n"
    : "+f"(d[0]), "+f"(d[1]), "+f"(d[2]), "+f"(d[3]), "+f"(d[4]), "+f"(d[5]), "+f"(d[6]), "+f"(d[7]), "+f"(d[8]), "+f"(d[9]), "+f"(d[10]), "+f"(d[11]), "+f"(d[12]), "+f"(d[13]), "+f"(d[14]), "+f"(d[15]), "+f"(d[16]), "+f"(d[17]), "+f"(d[18]), "+f"(d[19]), "+f"(d[20]), "+f"(d[21]), "+f"(d[22]), "+f"(d[23]), "+f"(d[24]), "+f"(d[25]), "+f"(d[26]), "+f"(d[27]), "+f"(d[28]), "+f"(d[29]), "+f"(d[30]), "+f"(d[31]), "+f"(d[32]), "+f"(d[33]), "+f"(d[34]), "+f"(d[35]), "+f"(d[36]), "+f"(d[37]), "+f"(d[38]), "+f"(d[39]), "+f"(d[40]), "+f"(d[41]), "+f"(d[42]), "+f"(d[43]), "+f"(d[44]), "+f"(d[45]), "+f"(d[46]), "+f"(d[47]), "+f"(d[48]), "+f"(d[49]), "+f"(d[50]), "+f"(d[51]), "+f"(d[52]), "+f"(d[53]), "+f"(d[54]), "+f"(d[55]), "+f"(d[56]), "+f"(d[57]), "+f"(d[58]), "+f"(d[59]), "+f"(d[60]), "+f"(d[61]), "+f"(d[62]), "+f"(d[63]) : "r"(a[0]), "r"(a[1]), "r"(a[2]), "r"(a[3]), "l"(db));
}
template<> __device__ __forceinline__ void wgmma_ss<0, 1, 0>(float* d, uint64_t da, uint64_t db) {
  asm volatile("{\n.reg .pred p;\nsetp.ne.b32 p, 0, 0;\n"
    "wgmma.mma_async.sync.aligned.m64n128k16.f32.bf16.bf16 {%0, %1, %2, %3, %4, %5, %6, %7, %8, %9, %10, %11, %12, %13, %14, %15, %16, %17, %18, %19, %20, %21, %22, %23, %24, %25, %26, %27, %28, %29, %30, %31, %32, %33, %34, %35, %36, %37, %38, %39, %40, %41, %42, %43, %44, %45, %46, %47, %48, %49, %50, %51, %52, %53, %54, %55, %56, %57, %58, %59, %60, %61, %62, %63}, %64, %65, p, 1, 1, 0, 1;\n}\n"
    : "=f"(d[0]), "=f"(d[1]), "=f"(d[2]), "=f"(d[3]), "=f"(d[4]), "=f"(d[5]), "=f"(d[6]), "=f"(d[7]), "=f"(d[8]), "=f"(d[9]), "=f"(d[10]), "=f"(d[11]), "=f"(d[12]), "=f"(d[13]), "=f"(d[14]), "=f"(d[15]), "=f"(d[16]), "=f"(d[17]), "=f"(d[18]), "=f"(d[19]), "=f"(d[20]), "=f"(d[21]), "=f"(d[22]), "=f"(d[23]), "=f"(d[24]), "=f"(d[25]), "=f"(d[26]), "=f"(d[27]), "=f"(d[28]), "=f"(d[29]), "=f"(d[30]), "=f"(d[31]), "=f"(d[32]), "=f"(d[33]), "=f"(d[34]), "=f"(d[35]), "=f"(d[36]), "=f"(d[37]), "=f"(d[38]), "=f"(d[39]), "=f"(d[40]), "=f"(d[41]), "=f"(d[42]), "=f"(d[43]), "=f"(d[44]), "=f"(d[45]), "=f"(d[46]), "=f"(d[47]), "=f"(d[48]), "=f"(d[49]), "=f"(d[50]), "=f"(d[51]), "=f"(d[52]), "=f"(d[53]), "=f"(d[54]), "=f"(d[55]), "=f"(d[56]), "=f"(d[57]), "=f"(d[58]), "=f"(d[59]), "=f"(d[60]), "=f"(d[61]), "=f"(d[62]), "=f"(d[63]) : "l"(da), "l"(db));
}
template<> __device__ __forceinline__ void wgmma_ss<1, 0, 0>(float* d, uint64_t da, uint64_t db) {
  asm volatile("{\n.reg .pred p;\nsetp.ne.b32 p, 0, 0;\n"
    "wgmma.mma_async.sync.aligned.m64n128k16.f32.bf16.bf16 {%0, %1, %2, %3, %4, %5, %6, %7, %8, %9, %10, %11, %12, %13, %14, %15, %16, %17, %18, %19, %20, %21, %22, %23, %24, %25, %26, %27, %28, %29, %30, %31, %32, %33, %34, %35, %36, %37, %38, %39, %40, %41, %42, %43, %44, %45, %46, %47, %48, %49, %50, %51, %52, %53, %54, %55, %56, %57, %58, %59, %60, %61, %62, %63}, %64, %65, p, 1, 1, 1, 0;\n}\n"
    : "=f"(d[0]), "=f"(d[1]), "=f"(d[2]), "=f"(d[3]), "=f"(d[4]), "=f"(d[5]), "=f"(d[6]), "=f"(d[7]), "=f"(d[8]), "=f"(d[9]), "=f"(d[10]), "=f"(d[11]), "=f"(d[12]), "=f"(d[13]), "=f"(d[14]), "=f"(d[15]), "=f"(d[16]), "=f"(d[17]), "=f"(d[18]), "=f"(d[19]), "=f"(d[20]), "=f"(d[21]), "=f"(d[22]), "=f"(d[23]), "=f"(d[24]), "=f"(d[25]), "=f"(d[26]), "=f"(d[27]), "=f"(d[28]), "=f"(d[29]), "=f"(d[30]), "=f"(d[31]), "=f"(d[32]), "=f"(d[33]), "=f"(d[34]), "=f"(d[35]), "=f"(d[36]), "=f"(d[37]), "=f"(d[38]), "=f"(d[39]), "=f"(d[40]), "=f"(d[41]), "=f"(d[42]), "=f"(d[43]), "=f"(d[44]), "=f"(d[45]), "=f"(d[46]), "=f"(d[47]), "=f"(d[48]), "=f"(d[49]), "=f"(d[50]), "=f"(d[51]), "=f"(d[52]), "=f"(d[53]), "=f"(d[54]), "=f"(d[55]), "=f"(d[56]), "=f"(d[57]), "=f"(d[58]), "=f"(d[59]), "=f"(d[60]), "=f"(d[61]), "=f"(d[62]), "=f"(d[63]) : "l"(da), "l"(db));
}
template<> __device__ __forceinline__ void wgmma_ss<0, 1, 1>(float* d, uint64_t da, uint64_t db) {
  asm volatile("{\n.reg .pred p;\nsetp.ne.b32 p, 1, 0;\n"
    "wgmma.mma_async.sync.aligned.m64n128k16.f32.bf16.bf16 {%0, %1, %2, %3, %4, %5, %6, %7, %8, %9, %10, %11, %12, %13, %14, %15, %16, %17, %18, %19, %20, %21, %22, %23, %24, %25, %26, %27, %28, %29, %30, %31, %32, %33, %34, %35, %36, %37, %38, %39, %40, %41, %42, %43, %44, %45, %46, %47, %48, %49, %50, %51, %52, %53, %54, %55, %56, %57, %58, %59, %60, %61, %62, %63}, %64, %65, p, 1, 1, 0, 1;\n}\n"
    : "+f"(d[0]), "+f"(d[1]), "+f"(d[2]), "+f"(d[3]), "+f"(d[4]), "+f"(d[5]), "+f"(d[6]), "+f"(d[7]), "+f"(d[8]), "+f"(d[9]), "+f"(d[10]), "+f"(d[11]), "+f"(d[12]), "+f"(d[13]), "+f"(d[14]), "+f"(d[15]), "+f"(d[16]), "+f"(d[17]), "+f"(d[18]), "+f"(d[19]), "+f"(d[20]), "+f"(d[21]), "+f"(d[22]), "+f"(d[23]), "+f"(d[24]), "+f"(d[25]), "+f"(d[26]), "+f"(d[27]), "+f"(d[28]), "+f"(d[29]), "+f"(d[30]), "+f"(d[31]), "+f"(d[32]), "+f"(d[33]), "+f"(d[34]), "+f"(d[35]), "+f"(d[36]), "+f"(d[37]), "+f"(d[38]), "+f"(d[39]), "+f"(d[40]), "+f"(d[41]), "+f"(d[42]), "+f"(d[43]), "+f"(d[44]), "+f"(d[45]), "+f"(d[46]), "+f"(d[47]), "+f"(d[48]), "+f"(d[49]), "+f"(d[50]), "+f"(d[51]), "+f"(d[52]), "+f"(d[53]), "+f"(d[54]), "+f"(d[55]), "+f"(d[56]), "+f"(d[57]), "+f"(d[58]), "+f"(d[59]), "+f"(d[60]), "+f"(d[61]), "+f"(d[62]), "+f"(d[63]) : "l"(da), "l"(db));
}
template<> __device__ __forceinline__ void wgmma_ss<1, 0, 1>(float* d, uint64_t da, uint64_t db) {
  asm volatile("{\n.reg .pred p;\nsetp.ne.b32 p, 1, 0;\n"
    "wgmma.mma_async.sync.aligned.m64n128k16.f32.bf16.bf16 {%0, %1, %2, %3, %4, %5, %6, %7, %8, %9, %10, %11, %12, %13, %14, %15, %16, %17, %18, %19, %20, %21, %22, %23, %24, %25, %26, %27, %28, %29, %30, %31, %32, %33, %34, %35, %36, %37, %38, %39, %40, %41, %42, %43, %44, %45, %46, %47, %48, %49, %50, %51, %52, %53, %54, %55, %56, %57, %58, %59, %60, %61, %62, %63}, %64, %65, p, 1, 1, 1, 0;\n}\n"
    : "+f"(d[0]), "+f"(d[1]), "+f"(d[2]), "+f"(d[3]), "+f"(d[4]), "+f"(d[5]), "+f"(d[6]), "+f"(d[7]), "+f"(d[8]), "+f"(d[9]), "+f"(d[10]), "+f"(d[11]), "+f"(d[12]), "+f"(d[13]), "+f"(d[14]), "+f"(d[15]), "+f"(d[16]), "+f"(d[17]), "+f"(d[18]), "+f"(d[19]), "+f"(d[20]), "+f"(d[21]), "+f"(d[22]), "+f"(d[23]), "+f"(d[24]), "+f"(d[25]), "+f"(d[26]), "+f"(d[27]), "+f"(d[28]), "+f"(d[29]), "+f"(d[30]), "+f"(d[31]), "+f"(d[32]), "+f"(d[33]), "+f"(d[34]), "+f"(d[35]), "+f"(d[36]), "+f"(d[37]), "+f"(d[38]), "+f"(d[39]), "+f"(d[40]), "+f"(d[41]), "+f"(d[42]), "+f"(d[43]), "+f"(d[44]), "+f"(d[45]), "+f"(d[46]), "+f"(d[47]), "+f"(d[48]), "+f"(d[49]), "+f"(d[50]), "+f"(d[51]), "+f"(d[52]), "+f"(d[53]), "+f"(d[54]), "+f"(d[55]), "+f"(d[56]), "+f"(d[57]), "+f"(d[58]), "+f"(d[59]), "+f"(d[60]), "+f"(d[61]), "+f"(d[62]), "+f"(d[63]) : "l"(da), "l"(db));
}


__device__ __forceinline__ uint32_t smem_u32(const void* p) { return (uint32_t)__cvta_generic_to_shared(p); }
__device__ __forceinline__ void wg_fence() { asm volatile("wgmma.fence.sync.aligned;" ::: "memory"); }
__device__ __forceinline__ void wg_commit() { asm volatile("wgmma.commit_group.sync.aligned;" ::: "memory"); }
template <int N> __device__ __forceinline__ void wg_wait() { asm volatile("wgmma.wait_group.sync.aligned %0;" ::"n"(N) : "memory"); }
__host__ __device__ constexpr uint64_t mkdesc(uint32_t addr, uint32_t lbo, uint32_t sbo, uint32_t swz) {
  return (uint64_t)((addr & 0x3FFFF) >> 4) | ((uint64_t)(lbo >> 4) << 16) | ((uint64_t)(sbo >> 4) << 32) | ((uint64_t)swz << 62);
}
__device__ __forceinline__ uint64_t mk64(uint32_t lo, uint32_t hi) { uint64_t d; asm("mov.b64 %0, {%1, %2};" : "=l"(d) : "r"(lo), "r"(hi)); return d; }
constexpr uint32_t SB0 = 1024;
__device__ __forceinline__ void mbar_init(uint32_t bar, int cnt) { asm volatile("mbarrier.init.shared::cta.b64 [%0], %1;" ::"r"(bar), "r"(cnt) : "memory"); }
__device__ __forceinline__ void mbar_expect_tx(uint32_t bar, uint32_t bytes) {
  asm volatile("mbarrier.arrive.expect_tx.shared::cta.b64 _, [%0], %1;" ::"r"(bar), "r"(bytes) : "memory");
}
__device__ __forceinline__ void mbar_arrive(uint32_t bar) { asm volatile("mbarrier.arrive.shared::cta.b64 _, [%0];" ::"r"(bar) : "memory"); }
__device__ __forceinline__ void mbar_arrive_remote(uint32_t bar) { asm volatile("mbarrier.arrive.shared::cluster.b64 _, [%0];" ::"r"(bar) : "memory"); }
constexpr int SPIN_LIMIT = 1 << 16;
__device__ __forceinline__ void mbar_wait(uint32_t bar, uint32_t parity) {
  asm volatile(
      "{\n.reg .pred p;\n.reg .u32 c;\n"
      "mov.u32 c, 0;\n"
      "LOOP%=:\n"
      "mbarrier.try_wait.parity.shared::cta.b64 p, [%0], %1;\n"
      "add.u32 c, c, 1;\n"
      "setp.gt.or.u32 p, c, 65535, p;\n"
      "@!p bra.uni LOOP%=;\n}\n" ::"r"(bar), "r"(parity) : "memory");
}
__device__ __forceinline__ void mbar_wait2(uint32_t bar0, uint32_t bar1) {
  asm volatile(
      "{\n.reg .pred p, q;\n.reg .u32 c;\n"
      "mov.u32 c, 0;\n"
      "LOOP%=:\n"
      "mbarrier.try_wait.parity.shared::cta.b64 p, [%0], 0;\n"
      "mbarrier.try_wait.parity.shared::cta.b64 q, [%1], 0;\n"
      "add.u32 c, c, 1;\n"
      "and.pred p, p, q;\n"
      "setp.gt.or.u32 p, c, 65535, p;\n"
      "@!p bra.uni LOOP%=;\n}\n" ::"r"(bar0), "r"(bar1) : "memory");
}
__device__ __forceinline__ void mbar_arrive_elect(uint32_t bar, bool cond = true) {
  asm volatile("{\n.reg .pred p, q;\nelect.sync _|p, 0xffffffff;\nsetp.ne.and.u32 q, %1, 0, p;\n@q mbarrier.arrive.shared::cta.b64 _, [%0];\n}\n" ::"r"(bar), "r"((uint32_t)cond) : "memory");
}
__device__ __forceinline__ void named_arrive_if(int id, int n, bool cond) {
  asm volatile("{\n.reg .pred q;\nsetp.ne.u32 q, %2, 0;\n@q bar.arrive %0, %1;\n}\n" ::"r"(id), "r"(n), "r"((uint32_t)cond) : "memory");
}
__device__ __forceinline__ uint32_t mapa(uint32_t addr, uint32_t rank) { uint32_t r; asm("mapa.shared::cluster.u32 %0, %1, %2;" : "=r"(r) : "r"(addr), "r"(rank)); return r; }
__device__ __forceinline__ uint32_t lds32(uint32_t a) { uint32_t v; asm volatile("ld.shared.b32 %0, [%1];" : "=r"(v) : "r"(a) : "memory"); return v; }
__device__ __forceinline__ uint4 lds128(uint32_t a) { uint4 v; asm volatile("ld.shared.v4.b32 {%0,%1,%2,%3}, [%4];" : "=r"(v.x), "=r"(v.y), "=r"(v.z), "=r"(v.w) : "r"(a) : "memory"); return v; }
__device__ __forceinline__ float2 lds64f(uint32_t a) { float2 v; asm volatile("ld.shared.v2.f32 {%0,%1}, [%2];" : "=f"(v.x), "=f"(v.y) : "r"(a) : "memory"); return v; }
__device__ __forceinline__ void sts64(uint32_t a, uint32_t x, uint32_t y) { asm volatile("st.shared.v2.b32 [%0], {%1,%2};" ::"r"(a), "r"(x), "r"(y) : "memory"); }
__device__ __forceinline__ void sts128(uint32_t a, uint4 v) { asm volatile("st.shared.v4.b32 [%0], {%1,%2,%3,%4};" ::"r"(a), "r"(v.x), "r"(v.y), "r"(v.z), "r"(v.w) : "memory"); }
__device__ __forceinline__ void st_async128(uint32_t a, uint32_t x, uint32_t y, uint32_t z, uint32_t w, uint32_t bar) {
  asm volatile("st.async.weak.shared::cluster.mbarrier::complete_tx::bytes.v4.b32 [%0], {%1,%2,%3,%4}, [%5];" ::"r"(a), "r"(x), "r"(y), "r"(z), "r"(w), "r"(bar) : "memory");
}
__device__ __forceinline__ void stsm4(uint32_t a, const uint32_t* r) {
  asm volatile("stmatrix.sync.aligned.m8n8.x4.shared.b16 [%0], {%1,%2,%3,%4};" ::"r"(a), "r"(r[0]), "r"(r[1]), "r"(r[2]), "r"(r[3]) : "memory");
}
__device__ __forceinline__ void stsm4t(uint32_t a, const uint32_t* r) {
  asm volatile("stmatrix.sync.aligned.m8n8.x4.trans.shared.b16 [%0], {%1,%2,%3,%4};" ::"r"(a), "r"(r[0]), "r"(r[1]), "r"(r[2]), "r"(r[3]) : "memory");
}
__device__ __forceinline__ uint32_t hfma2(uint32_t a, uint32_t b, uint32_t c) { uint32_t d; asm("fma.rn.bf16x2 %0, %1, %2, %3;" : "=r"(d) : "r"(a), "r"(b), "r"(c)); return d; }
__device__ __forceinline__ uint32_t hmul2(uint32_t a, uint32_t b) { uint32_t d; asm("mul.rn.bf16x2 %0, %1, %2;" : "=r"(d) : "r"(a), "r"(b)); return d; }
__device__ __forceinline__ uint32_t pack_bf16(float lo, float hi) { uint32_t d; asm("cvt.rn.bf16x2.f32 %0, %1, %2;" : "=r"(d) : "f"(hi), "f"(lo)); return d; }
__device__ __forceinline__ void named_bar(int id, int n) { asm volatile("bar.sync %0, %1;" ::"r"(id), "r"(n) : "memory"); }
__device__ __forceinline__ void named_arrive(int id, int n) { asm volatile("bar.arrive %0, %1;" ::"r"(id), "r"(n) : "memory"); }
__device__ __forceinline__ void fence_async_smem() { asm volatile("fence.proxy.async.shared::cta;" ::: "memory"); }
__device__ __forceinline__ void tma2d(uint32_t dst, const CUtensorMap* tm, uint32_t bar, int c0, int c1) {
  asm volatile("cp.async.bulk.tensor.2d.shared::cluster.global.mbarrier::complete_tx::bytes [%0], [%1, {%3, %4}], [%2];" ::"r"(dst), "l"(tm), "r"(bar), "r"(c0), "r"(c1) : "memory");
}
__device__ __forceinline__ void dsmem_copy(uint32_t dst, uint32_t src, uint32_t bytes, uint32_t bar) {
  asm volatile("cp.async.bulk.shared::cluster.shared::cta.mbarrier::complete_tx::bytes [%0], [%1], %2, [%3];" ::"r"(dst), "r"(src), "r"(bytes), "r"(bar) : "memory");
}
__device__ __forceinline__ void global_arrive(unsigned* cnt) { asm volatile("red.release.gpu.global.add.u32 [%0], 1;" ::"l"(cnt) : "memory"); }
__device__ __forceinline__ void global_wait(unsigned* cnt, unsigned n) {
  unsigned v; int it = 0;
  do { asm volatile("ld.acquire.gpu.global.u32 %0, [%1];" : "=r"(v) : "l"(cnt) : "memory"); } while ((v & (n - 1)) != 0 && ++it < SPIN_LIMIT);
}

constexpr uint32_t OFF_AH0 = 0, OFF_RING = 81920, OFF_AH1 = 147456, OFF_MISC = 229376, SMEM_BYTES = 232448;
constexpr uint32_t U_PAR = 288, U_CH = 576, U_SEG = 2880, F_CH = 4352, F_HALF = 2176, OFF_F = OFF_AH1, OFF_U = OFF_F + 5 * F_CH + 2528, OFF_OBOX = OFF_U + 16 * U_SEG;
static_assert(OFF_OBOX + 4 * U_SEG <= OFF_MISC, "conv data must fit");
constexpr uint32_t BAR_KV = OFF_MISC, BAR_U = OFF_MISC + 64, BAR_EMPTY = OFF_MISC + 128, BAR_AFULL = OFF_MISC + 160, BAR_ZFULL = OFF_MISC + 240,
                   BAR_HFULL = OFF_MISC + 320, BAR_AFREE = OFF_MISC + 368, BAR_X = OFF_MISC + 392, BAR_ZREAD = OFF_MISC + 400, BAR_LN = OFF_MISC + 408,
                   BAR_STG = OFF_MISC + 416, BAR_SFREE = OFF_MISC + 280, BAR_T2D = OFF_MISC + 288, BAR_ZREADE = OFF_MISC + 296, BAR_LNE = OFF_MISC + 304, BAR_CDONE = OFF_MISC + 312, BAR_FULL = OFF_MISC + 456, BAR_STG2 = OFF_MISC + 848, BAR_UOWN = OFF_MISC + 2432;
constexpr uint32_t OFF_STAT = OFF_MISC + 896;
enum { NB_WG0 = 1, NB_H2 = 6, NB_ZDONE = 5, NB_TOK = 12, NB_H01 = 7, NB_H10 = 8, NB_HST = 9, NB_INIT = 10, NB_ZE = 11 };

__device__ uint4 g_z[D_ * 256];
__device__ unsigned g_cnt[2048];
constexpr int CNT_EARLY = 32 * 17, CNT_LATE = 1024;

__device__ __forceinline__ bool elect_one() {
  uint32_t r; asm volatile("{.reg .pred p; elect.sync _|p, 0xffffffff; selp.u32 %0, 1, 0, p;}" : "=r"(r)); return r;
}
struct Ids { uint32_t rank, cid; int t, wg, warp, lane, rb, quarter; };
__device__ __forceinline__ Ids get_ids() {
  Ids d; uint32_t tid;
  asm volatile("mov.u32 %0, %tid.x;" : "=r"(tid));
  uint32_t bid;
  asm volatile("mov.u32 %0, %ctaid.x;" : "=r"(bid));
  d.rank = bid & 1; d.cid = bid >> 1;
  const int w = __shfl_sync(0xffffffffu, tid >> 5, 0);
  d.t = tid & 127; d.wg = w >> 2; d.warp = w & 3; d.lane = tid & 31;
  const uint32_t cid = d.cid;
  const int q7 = (int)((cid - 36) * 37) >> 8;
  d.rb = cid < 4 ? 0 : cid < 36 ? 1 + ((cid - 4) & 7) : (int)cid - 27 - 7 * q7;
  d.quarter = cid < 4 ? cid : cid < 36 ? (cid - 4) >> 3 : q7;
  return d;
}
struct Params { const bf16 *q, *shift, *f, *D, *w1, *w3, *w2; bf16* out; uint4* z; unsigned* cnt; };
struct Maps { CUtensorMap k16, k32, v16, v32, x, z, out, w1, w3, w2; };

template <int N> __device__ __forceinline__ void pin(float* d) {
#pragma unroll
  for (int i = 0; i < N; i++) { float nv; asm volatile("mov.b32 %0, %1;" : "=f"(nv) : "f"(d[i])); d[i] = nv; }
}
struct ABase { uint32_t n, lo, hi; };
template <int I, int S> __device__ __forceinline__ void conv_load1(uint32_t* a, const ABase& ab, uint32_t off) {
  const uint32_t o = off + (S & 1) * 32 + (S >> 1) * 128 + 2 * U_SEG * I;
  const uint32_t lo = S ? ab.n : ab.lo, hi = S ? ab.n - 16 : ab.hi;
  a[0] = lds32(lo + o); a[1] = lds32(lo + o + U_SEG); a[2] = lds32(hi + o); a[3] = lds32(hi + o + U_SEG);
}
template <int I, int S> __device__ __forceinline__ void conv_mma1(float* acc, const uint32_t* a, uint64_t flo) {
  wgmma_rs<128 - 16 * I, (I == 0 && S == 0) ? 0 : 1>(acc, a, flo + (16 * I + (S & 1) + 4 * (S >> 1)));
}
__device__ __forceinline__ uint4 ldg128(const uint4* p) {
  uint4 v; asm volatile("ld.global.nc.v4.b32 {%0,%1,%2,%3}, [%4];" : "=r"(v.x), "=r"(v.y), "=r"(v.z), "=r"(v.w) : "l"(p)); return v;
}
struct FStore { uint32_t addr, dd; int wg; bool first; };
__device__ __forceinline__ void f_store(uint4* ld, uint32_t dd, const FStore& fs) {
  if (fs.first) {
    const float x = __uint_as_float(ld[0].x << 16) + __uint_as_float(dd << 16);
    ld[0].x = (ld[0].x & 0xffff0000u) | (pack_bf16(x, 0.f) & 0xffffu);
  }
  sts128(fs.addr + 1024, ld[0]);
  sts128(fs.addr, ld[1]);
}
struct ConvOut { uint4* zdst; int srclane, zstep; bool a0, q0; };
template <int I> __device__ __forceinline__ void conv_out_a(const float* acc, float* pend, const ConvOut& o) {
#pragma unroll
  for (int e = 0; e < 2; e++) {
    const int c = 2 * (7 - I);
    float v0 = acc[4 * c + e] + acc[4 * (c + 1) + 2 + e];
    float v1 = (c + 2 < 16) ? acc[4 * (c + 1) + e] + acc[4 * (c + 2) + 2 + e] : acc[4 * (c + 1) + e];
    float v2 = (c + 2 < 16) ? acc[4 * (c + 2) + e] + acc[4 * (c + 3) + 2 + e] : 0.f;
    float send = (o.a0 && !o.q0) ? v0 : v1;
    pend[e] = o.a0 ? (o.q0 ? v2 : v1) : v0;
    pend[2 + e] = __shfl_sync(0xffffffffu, send, o.srclane);
  }
}
template <int I> __device__ __forceinline__ void conv_out_b(const float* pend, uint32_t* w, const ConvOut& o, int zoff) {
  asm volatile("{\n.reg .f32 a, b;\nadd.f32 a, %1, %3;\nadd.f32 b, %2, %4;\ncvt.rn.bf16x2.f32 %0, a, b;\n}\n" : "=r"(w[I & 3]) : "f"(pend[0]), "f"(pend[1]), "f"(pend[2]), "f"(pend[3]));
  if ((I & 3) == 3) o.zdst[zoff + (I >> 2) * 256] = make_uint4(w[0], w[1], w[2], w[3]);
}
constexpr int SW3 = 10;
template <int G> struct CBuf { static constexpr int v = G <= SW3 ? (G & 1) : (G == SW3 + 1 ? 2 : CBuf<(G > SW3 + 1 ? G - 3 : 0)>::v); };
template <> struct CBuf<0> { static constexpr int v = 0; };
template <int N> __device__ __forceinline__ void conv2_load(uint32_t (*a)[8], float (*pend)[4], uint32_t (*w)[4], const ConvOut& o, const ABase& abase, uint32_t sb) {
  if constexpr ((N & 3) == 0) {
    mbar_wait2(sb + BAR_UOWN + 8 * (N < 32 ? N >> 2 : 7), sb + BAR_U + 8 * (N < 32 ? N >> 2 : 7));
  }
  if constexpr (N < 32) {
    conv_load1<(N >> 2), 2 * (N & 1)>(a[CBuf<N>::v], abase, ((N >> 1) & 1) * U_CH);
    conv_load1<(N >> 2), 2 * (N & 1) + 1>(a[CBuf<N>::v] + 4, abase, ((N >> 1) & 1) * U_CH);
  }
  if constexpr ((N & 3) == 0 && N >= 8) {
    conv_out_b<(N >> 2) - 2>(pend[0], w[0], o, 0); conv_out_b<(N >> 2) - 2>(pend[1], w[1], o, o.zstep);
    if constexpr (N == 20) named_arrive(NB_ZE, 384 + 32);
  }
}
template <int G> __device__ __forceinline__ void conv2(float (*acc)[64], uint32_t (*a)[8], float (*pend)[4], uint32_t (*w)[4], const ConvOut& o, const ABase& abase, uint64_t flo, uint32_t sb, uint4* ld, const FStore& fs) {
  constexpr int I = G >> 2, c = (G >> 1) & 1, H = G & 1;
  if constexpr (G == 2) named_bar(NB_WG0 + fs.wg, 128);
  if constexpr (G == 0) conv2_load<0>(a, pend, w, o, abase, sb);
  if constexpr (G > SW3) wg_wait<1>();
  if constexpr (G >= SW3 && G < 31) conv2_load<G + 1>(a, pend, w, o, abase, sb);
  if constexpr (H == 0 && I > 0) pin<64 - 8 * (I - 1)>(acc[c]);
  wg_fence();
  conv_mma1<I, 2 * H>(acc[c], a[CBuf<G>::v], flo + c * (F_CH >> 4));
  conv_mma1<I, 2 * H + 1>(acc[c], a[CBuf<G>::v] + 4, flo + c * (F_CH >> 4));
  wg_commit();
  if constexpr (G == 1) { f_store(ld, fs.dd, fs); fence_async_smem(); }
  if constexpr (H == 0 && I > 0) conv_out_a<I - 1>(acc[c], pend[c], o);
  if constexpr (G < SW3) { if constexpr (G > 0) wg_wait<1>(); conv2_load<G + 1>(a, pend, w, o, abase, sb); }
  if constexpr (G < 31) conv2<G + 1>(acc, a, pend, w, o, abase, flo, sb, ld, fs); else conv2_load<32>(a, pend, w, o, abase, sb);
}
template <int G> __device__ __forceinline__ void conv1(float* acc, uint32_t (*a)[4], float* pend, uint32_t* w, const ConvOut& o, const ABase& abase, uint64_t flo, uint32_t sb) {
  constexpr int I = G >> 2, S = G & 3, N = G + 1;
  if constexpr (G >= 0) {
    if constexpr (S == 0 && I > 0) { wg_wait<0>(); pin<64 - 8 * (I - 1)>(acc); }
    wg_fence();
    conv_mma1<I, S>(acc, a[G & 1], flo);
    wg_commit();
    if constexpr (S == 1 && I > 0) conv_out_a<I - 1>(acc, pend, o);
  }
  if constexpr ((N & 3) == 0) mbar_wait2(sb + BAR_UOWN + 8 * (N < 32 ? N >> 2 : 7), sb + BAR_U + 8 * (N < 32 ? N >> 2 : 7));
  if constexpr (N < 32) {
    if constexpr (G >= 1 && S != 0) wg_wait<1>();
    conv_load1<(N >> 2), (N & 3)>(a[N & 1], abase, 0);
  }
  if constexpr ((N & 3) == 0 && N >= 8) {
    conv_out_b<(N >> 2) - 2>(pend, w, o, 0);
    if constexpr (N == 20) named_arrive(NB_ZE, 384 + 32);
  }
  if constexpr (N < 32) conv1<N>(acc, a, pend, w, o, abase, flo, sb);
}

__device__ __forceinline__ void issue_kv(const Maps& tm, uint32_t sb, uint32_t rank, bool wide, int w0, int i) {
  const uint32_t box = wide ? 8704 : 4352, dst = sb + OFF_AH1 - (8 - i) * 2 * box, bar = sb + BAR_KV + 8 * i;
  const int r0 = 32 * i + 16 * (int)rank - 1;
  asm volatile("cp.async.bulk.tensor.3d.shared::cluster.global.mbarrier::complete_tx::bytes [%0], [%1, {%3, %4, %5}], [%2];" ::"r"(dst), "l"(wide ? &tm.k32 : &tm.k16), "r"(bar), "r"(w0), "r"(r0), "r"(0) : "memory");
  asm volatile("cp.async.bulk.tensor.3d.shared::cluster.global.mbarrier::complete_tx::bytes [%0], [%1, {%3, %4, %5}], [%2];" ::"r"(dst + box), "l"(wide ? &tm.v32 : &tm.v16), "r"(bar), "r"(w0), "r"(r0), "r"(0) : "memory");
}
template <int NCH> __device__ __forceinline__ void conv_role(const Maps& tm, const Params& p, uint32_t sb) {
  if (NCH == 2) asm volatile("setmaxnreg.inc.sync.aligned.u32 184;"); else asm volatile("setmaxnreg.dec.sync.aligned.u32 104;");
  uint4 ld[2 * NCH]; uint32_t ddl;
  {
    const int ch0 = 5 * blockIdx.x + 2 * (threadIdx.x >> 7);
#pragma unroll
    for (int i = 0; i < 2; i++) ld[i] = ldg128(reinterpret_cast<const uint4*>(p.f + (size_t)ch0 * S_) + (threadIdx.x & 127) + 128 * i);
    asm volatile("ld.global.nc.u16 %0, [%1];" : "=r"(ddl) : "l"(p.D + ch0 + (threadIdx.x & (NCH - 1))));
  }
  const Ids id = get_ids();
  const uint32_t rank = id.rank, cid = id.cid; const int wg = id.wg, t = id.t, lane = id.lane, warp = id.warp;
  const int lc = 2 * wg, ch = 10 * cid + 5 * rank + lc;
  asm volatile("barrier.cluster.arrive.relaxed.aligned;" ::: "memory");
  if (lane == 0) {
    if (NCH == 2) {
      const uint32_t b0 = sb + BAR_FULL + 48 * (wg * 4 + warp);
#pragma unroll 1
      for (int i = 0; i < 6; i++) { mbar_init(b0 + 8 * i, 1); mbar_expect_tx(b0 + 8 * i, 16384); }
    } else if (warp < 3) {
#pragma unroll 1
      for (int i = 0; i < 5; i++) { mbar_init(sb + BAR_AFULL + 40 * warp + 8 * i, 1); mbar_expect_tx(sb + BAR_AFULL + 40 * warp + 8 * i, warp < 2 ? 8192 : 20480); }
      mbar_init(sb + BAR_HFULL + 16 * warp, 4); mbar_init(sb + BAR_HFULL + 16 * warp + 8, 1); mbar_expect_tx(sb + BAR_HFULL + 16 * warp + 8, 16384);
      mbar_init(sb + BAR_AFREE + 8 * warp, 8);
    } else {
#pragma unroll
      for (int i = 0; i < 4; i++) mbar_init(sb + BAR_EMPTY + 8 * i, 4);
#pragma unroll
      for (int i = 0; i < 5; i++) { mbar_init(sb + BAR_STG + 8 * i, 4); mbar_init(sb + BAR_STG2 + 8 * i, 4); }
      mbar_init(sb + BAR_LN, 12); mbar_init(sb + BAR_LNE, 12); mbar_init(sb + BAR_CDONE, 1); mbar_init(sb + BAR_SFREE, 1); mbar_init(sb + BAR_T2D, 4);
    }
    asm volatile("fence.mbarrier_init.release.cluster;" ::: "memory");
  }
  __syncwarp();
  named_arrive(NB_INIT, 512);
  const bool early = ((10 * cid) & 63) > 54;
  const uint32_t fb = sb + OFF_F + lc * F_CH, ub = sb + OFF_U + lc * U_CH;
#pragma unroll
  for (int c = 0; c < NCH; c++) {
    if (t < 16) sts128(fb + c * F_CH + (t & 1) * F_HALF + 2048 + (t >> 1) * 16, make_uint4(0, 0, 0, 0));
    else if (t < 20) sts128(ub - U_SEG + 224 + c * U_CH + (t & 1) * U_PAR + ((t >> 1) & 1) * 16, make_uint4(0, 0, 0, 0));
  }
  FStore fs; fs.addr = fb + (t & 1) * F_HALF + (63 - (t >> 1)) * 16; fs.first = t == 0; fs.wg = wg;
  f_store(ld, __shfl_sync(0xffffffffu, ddl, 0), fs);
  fs.addr += F_CH; fs.dd = __shfl_sync(0xffffffffu, ddl, NCH - 1);
  fence_async_smem();
  asm volatile("barrier.cluster.wait.aligned;" ::: "memory");
  named_bar(NB_WG0 + wg, 128);
  if (NCH == 2) {
#pragma unroll
    for (int i = 2; i < 2 * NCH; i++)
      asm volatile("ld.global.v4.b32 {%0,%1,%2,%3}, [%4];" : "=r"(ld[i].x), "=r"(ld[i].y), "=r"(ld[i].z), "=r"(ld[i].w) : "l"(reinterpret_cast<const uint4*>(p.f + (size_t)ch * S_) + t + 128 * i) : "memory");
  }
  if (NCH == 1 && warp == 0 && !early) {
    const int c0 = 10 * cid, w0 = c0 & ~15;
    if (elect_one()) issue_kv(tm, sb, rank, (c0 + 10 - w0) > 16, w0, 2);
    __syncwarp();
    mbar_wait(sb + BAR_KV, 0);
    if (elect_one()) issue_kv(tm, sb, rank, (c0 + 10 - w0) > 16, w0, 3);
    __syncwarp();
  }
  if (NCH == 1 && warp == 1 && lane < 6) asm volatile("prefetch.tensormap [%0];" ::"l"(&tm.x + lane) : "memory");
  const int g = lane >> 2, q = lane & 3, b = 4 * warp + (g & 3), a0 = g >> 2;
  const int wi = (b >> 1) + 16 * a0 - q;
  ABase abase;
  abase.n = ub + (b & 1) * U_PAR + 4 * wi;
  abase.lo = abase.n - (wi < 0 ? U_SEG - 256 : 0);
  abase.hi = abase.n - 16 - (wi < 4 ? U_SEG - 256 : 0);
  const uint64_t flo = mkdesc(SB0 + OFF_F, F_HALF, 128, 0) + lc * (F_CH >> 4);
  const int qe = a0 ? (q + 3) & 3 : q, qr = 3 - qe;
  ConvOut o;
  o.srclane = a0 ? ((g & 3) << 2) | qe : (((g & 3) + 4) << 2) | ((q + 1) & 3);
  o.zdst = p.z + (ch >> 1) * 512 + (ch & 1) * 4 + (qr | ((1 - a0) << 3) | (b << 4));
  o.zstep = (ch & 1) ? 508 : 4;
  o.a0 = a0; o.q0 = q == 0;
  float acc[NCH][64];
  uint32_t w[NCH][4];
  float pend[NCH][4];
  if constexpr (NCH == 2) {
    uint32_t a[3][8];
    conv2<0>(acc, a, pend, w, o, abase, flo, sb, ld + 2, fs);
    pin<8>(acc[0]); conv_out_a<7>(acc[0], pend[0], o); conv_out_b<7>(pend[0], w[0], o, 0);
    wg_wait<0>(); pin<8>(acc[1]); conv_out_a<7>(acc[1], pend[1], o); conv_out_b<7>(pend[1], w[1], o, o.zstep);
  } else {
    uint32_t a[2][4];
    conv1<-1>(acc[0], a, pend[0], w[0], o, abase, flo, sb);
    wg_wait<0>(); pin<8>(acc[0]); conv_out_a<7>(acc[0], pend[0], o); conv_out_b<7>(pend[0], w[0], o, 0);
  }
  named_arrive(NB_ZDONE, 384 + 32);
}

__device__ __forceinline__ void stat_mma(float* c, uint32_t zero, uint32_t x0, uint32_t x1) {
  asm volatile("{\n.reg .b32 a0, a2;\nxor.b32 a0, %4, %7;\nmad.lo.u32 a2, %7, %7, %5;\n"
               "mma.sync.aligned.m16n8k16.row.col.f32.bf16.bf16.f32 {%0,%1,%2,%3}, {a0,%6,a2,%6}, {%4,%5}, {%0,%1,%2,%3};\n}\n"
               : "+f"(c[0]), "+f"(c[1]), "+f"(c[2]), "+f"(c[3]) : "r"(x0), "r"(x1), "r"(0x3f803f80u), "r"(zero));
}
template <int NQ> __device__ __forceinline__ void stat_partial(const uint4* v, uint32_t aq, uint32_t dst, int g, int q) {
  float c[4][4];
#pragma unroll
  for (int i = 0; i < 4; i++) c[0][i] = c[1][i] = c[2][i] = c[3][i] = 0.f;
#pragma unroll
  for (int u = 0; u < NQ; u++) { stat_mma(c[2 * (u & 1)], aq, v[u].x, v[u].y); stat_mma(c[2 * (u & 1) + 1], aq, v[u].z, v[u].w); }
  float r[4];
#pragma unroll
  for (int i = 0; i < 4; i++) r[i] = (c[0][i] + c[1][i]) + (c[2][i] + c[3][i]);
  if (q == (g >> 1)) sts64(dst, __float_as_uint((g & 1) ? r[3] : r[2]), __float_as_uint((g & 1) ? r[1] : r[0]));
}
__device__ __forceinline__ void stat_final(uint32_t src, float post, uint32_t& r2, uint32_t& c2) {
  const float2 a = lds64f(src), b = lds64f(src + 256), c = lds64f(src + 512);
  const float mean = (a.x + b.x + c.x) * (1.f / 640.f);
  const float var = fmaxf((a.y + b.y + c.y) * (1.f / 640.f) - mean * mean, 0.f);
  const float rs = rsqrtf(var + 1e-5f) * post;
  r2 = pack_bf16(rs, rs);
  const float sh = -mean * __uint_as_float(r2 << 16);
  c2 = pack_bf16(sh, sh);
}
__device__ __forceinline__ void stg128_if(uint4* ptr, const uint4& v, bool cond) {
  asm volatile("{\n.reg .pred p;\nsetp.ne.u32 p, %5, 0;\n@p st.global.v4.b32 [%0], {%1,%2,%3,%4};\n}\n" ::"l"(ptr), "r"(v.x), "r"(v.y), "r"(v.z), "r"(v.w), "r"((uint32_t)cond) : "memory");
}
__device__ __forceinline__ uint4 ldsm4t(uint32_t a) {
  uint4 v; asm volatile("ldmatrix.sync.aligned.m8n8.x4.trans.shared.b16 {%0,%1,%2,%3}, [%4];" : "=r"(v.x), "=r"(v.y), "=r"(v.z), "=r"(v.w) : "r"(a) : "memory"); return v;
}
__device__ __forceinline__ uint4 fma4(const uint4& a, uint32_t r, uint32_t c) { return make_uint4(hfma2(a.x, r, c), hfma2(a.y, r, c), hfma2(a.z, r, c), hfma2(a.w, r, c)); }

template <int NC> __device__ __forceinline__ void ln_role(const Params& p, uint32_t sb, const Ids& id) {
  const uint32_t rank = id.rank; const int wg = id.wg, lane = id.lane, warp = id.warp, rb = id.rb, quarter = id.quarter;
  const int g = lane >> 2, q = lane & 3, rho = 4 * (g & 1) + (g >> 1);
  int chunk[NC];
#pragma unroll
  for (int i = 0; i < NC; i++) chunk[i] = NC == 2 ? 2 * quarter + i : (4 * wg + i < 2 * quarter ? 4 * wg + i : 4 * wg + i + 2);
  const uint32_t xaddr = sb + OFF_AH0 + warp * 1024 + rho * 128 + ((q ^ rho) << 4);
  const uint32_t part = sb + OFF_STAT + warp * 64 + g * 8;
  uint4 x[2][2 * NC], h[2][2 * NC];
  uint32_t r2, c2, aq;
  asm volatile("mov.u32 %0, %ctaid.y;" : "=r"(aq));
  mbar_wait(sb + BAR_X, 0);
#pragma unroll
  for (int hf = 0; hf < 2; hf++) {
#pragma unroll
    for (int u = 0; u < 2 * NC; u++) x[hf][u] = lds128((xaddr ^ ((u & 1) << 6)) + chunk[u >> 1] * 8192 + hf * 4096);
    stat_partial<2 * NC>(x[hf], aq, part + hf * 768 + wg * 256, g, q);
  }
  named_bar(NB_TOK + warp, 96);
#pragma unroll
  for (int hf = 0; hf < 2; hf++) {
    stat_final(part + hf * 768, 1.f, r2, c2);
#pragma unroll
    for (int u = 0; u < 2 * NC; u++) h[hf][u] = fma4(x[hf][u], r2, c2);
  }
  named_bar(NB_TOK + warp, 96);
  const int zr = (lane >> 1) & 3;
  const uint32_t zaddr = sb + OFF_AH1 + (lane >> 3) * 1024 + zr * 128 + (((4 * (lane & 1) + warp) ^ zr) << 4);
#pragma unroll
  for (int hf = 0; hf < 2; hf++) {
    mbar_wait2(sb + BAR_ZFULL + 16 * hf, sb + BAR_ZFULL + 16 * hf + 8);
#pragma unroll
    for (int u = 0; u < 2 * NC; u++) {
      const uint4 z = ldsm4t((zaddr ^ ((u & 1) * 576)) + chunk[u >> 1] * 4096 + hf * 40960);
      h[hf][u].x = hfma2(h[hf][u].x, z.x, x[hf][u].x); h[hf][u].y = hfma2(h[hf][u].y, z.y, x[hf][u].y);
      h[hf][u].z = hfma2(h[hf][u].z, z.z, x[hf][u].z); h[hf][u].w = hfma2(h[hf][u].w, z.w, x[hf][u].w);
    }
    stat_partial<2 * NC>(h[hf], aq, part + hf * 768 + wg * 256, g, q);
    named_bar(NB_TOK + warp, 96);
    if (NC == 2 && lane == 0) mbar_arrive_remote(mapa(sb + (hf ? BAR_ZREAD : BAR_ZREADE), rank ^ 1));
    stat_final(part + hf * 768, 0.5f, r2, c2);
#pragma unroll
    for (int u = 0; u < 2 * NC; u++) sts128((xaddr ^ ((u & 1) << 6)) + chunk[u >> 1] * 8192 + hf * 4096, fma4(h[hf][u], r2, c2));
    fence_async_smem();
    __syncwarp();
    mbar_arrive_elect(sb + (hf ? BAR_LN : BAR_LNE));
  }
  uint4* hdst = reinterpret_cast<uint4*>(p.out + (size_t)(128 * rank + rb + 256 * (g >> 1) + 16 * (g & 1) + 32 * warp) * D_) + q;
  if (NC == 2) {
#pragma unroll
    for (int hf = 0; hf < 2; hf++)
#pragma unroll
      for (int u = 0; u < 4; u++) {
        mbar_wait(sb + BAR_FULL + 8 * (12 + 4 * hf + u), 0);
        hdst[hf * 1024 * (D_ / 8) + 16 * quarter + 4 * u] = h[hf][u];
      }
    named_bar(NB_HST, 256);
  } else {
    if (wg == 1) {
#pragma unroll
      for (int u = 4; u < 2 * NC; u++)
      { stg128_if(hdst + 48 + 4 * u, h[0][u], u == 4 + quarter); stg128_if(hdst + 1024 * (D_ / 8) + 48 + 4 * u, h[1][u], u == 4 + quarter); }
      named_arrive(NB_HST, 256);
    }
  }
}

__device__ __forceinline__ float silu_mul(float hg, float hu) {
  float r;
  asm volatile("{\n.reg .f32 t, x;\ntanh.approx.f32 t, %1;\nmul.f32 x, %1, %2;\nmul.f32 x, x, 0f40000000;\nfma.rn.f32 %0, x, t, x;\n}\n" : "=f"(r) : "f"(hg), "f"(hu));
  return r;
}
template <int P> __device__ __forceinline__ void hh_store(const uint32_t* hh, uint32_t base, bool cond = true) {
  asm volatile("{\n.reg .pred p;\nsetp.ne.u32 p, %5, 0;\n@p stmatrix.sync.aligned.m8n8.x4.shared.b16 [%0], {%1,%2,%3,%4};\n}\n" ::"r"((base ^ ((P & 3) << 5)) + (P >> 2) * 8192),
               "r"(hh[4 * P]), "r"(hh[4 * P + 1]), "r"(hh[4 * P + 2]), "r"(hh[4 * P + 3]), "r"((uint32_t)cond) : "memory");
}
template <int P> __device__ __forceinline__ void g1_piece(const float* acc, uint32_t* hh, uint32_t base, bool cond) {
#pragma unroll
  for (int i = 4 * (P & 3); i < 4 * (P & 3) + 4; i++)
    hh[(P & 4) * 4 + i] = pack_bf16(silu_mul(acc[2 * i], acc[32 + 2 * i]), silu_mul(acc[2 * i + 1], acc[33 + 2 * i]));
  hh_store<P>(hh, base, cond);
}
template <int HF> __device__ __forceinline__ void hh_ready(uint32_t sb, uint32_t rank, int slot, int warp) {
  fence_async_smem();
  __syncwarp();
  if (elect_one()) {
    const uint32_t o = slot * 16384 + warp * 2048;
    dsmem_copy(mapa(sb + OFF_AH1 + o + (1 - HF) * 8192, rank ^ 1), sb + OFF_AH0 + o + HF * 8192, 2048, mapa(sb + BAR_HFULL + 16 * slot + 8, rank ^ 1));
    if (HF) mbar_arrive(sb + BAR_HFULL + 16 * slot);
  }
}
#define DLO_AH0 (mkdesc(SB0 + OFF_AH0, 16, 1024, 1) + blockIdx.y)
#define DLO_AH1 (DLO_AH0 + (OFF_AH1 >> 4))
#define DLO_RING (mkdesc(SB0 + OFF_RING, 8192, 1024, 1) + blockIdx.y)
__device__ __forceinline__ void g1_issue(float (*acc)[64], int kc, int st) {
  const uint64_t al = (uint32_t)(kc * 512), bl = DLO_RING + (uint32_t)(st * 1024);
  wg_fence();
#pragma unroll
  for (int ks = 0; ks < 4; ks++) {
    wgmma_ss<0, 1, 1>(acc[0], (DLO_AH0 + al + ks * 2), (bl + ks * 128));
    wgmma_ss<0, 1, 1>(acc[1], (DLO_AH1 + al + ks * 2), (bl + ks * 128));
  }
  wg_commit();
}
template <int KC> __device__ __forceinline__ void g1_t2_step(float (*acc)[64], const uint32_t* hh, uint32_t hbase, uint32_t sb, uint32_t rank, int warp) {
  mbar_wait(sb + BAR_FULL + 8 * (20 + KC), 0);
  g1_issue(acc, KC, KC & 3);
  if (KC == 5) { mbar_wait(sb + BAR_AFREE + 8, 0); hh_store<0>(hh, hbase + 16384); hh_store<1>(hh, hbase + 16384); hh_store<2>(hh, hbase + 16384); hh_store<3>(hh, hbase + 16384); }
  if (KC == 6) { hh_ready<0>(sb, rank, 1, warp); hh_store<4>(hh, hbase + 16384); hh_store<5>(hh, hbase + 16384); hh_store<6>(hh, hbase + 16384); hh_store<7>(hh, hbase + 16384); }
  wg_wait<1>();
  if (elect_one()) {
    mbar_arrive(sb + BAR_EMPTY + 8 * ((KC - 1) & 3));
    if (!(KC & 1)) { const uint32_t b = sb + BAR_AFREE + 4 * KC - 8; mbar_arrive(b); mbar_arrive_remote(mapa(b, rank ^ 1)); }
  }
}
template <int FIRST> __device__ __forceinline__ void g1_half(float* acc, uint64_t da, uint64_t db) {
  wgmma_ss<0, 1, FIRST ? 0 : 1>(acc, da, db);
#pragma unroll
  for (int ks = 1; ks < 4; ks++) wgmma_ss<0, 1, 1>(acc, da + ks * 2, db + ks * 128);
}
__device__ __forceinline__ void g1_tile(float (*acc)[64], uint32_t* hh, uint32_t hbase, uint32_t sb, uint32_t rank, int tau, int wg, int warp) {
  {
    const int st0 = tau & 1, st1 = tau == 2 ? 1 : tau + 2;
    const uint64_t b0 = DLO_RING + (uint32_t)(st0 * 1024), b1 = DLO_RING + (uint32_t)(st1 * 1024);
    mbar_wait2(sb + BAR_FULL + (tau == 2 ? 160 : 8 * tau), sb + BAR_LN);
    if (tau) named_bar(tau == 1 ? NB_H01 : NB_H10, 256);
    wg_fence();
    g1_half<1>(acc[0], DLO_AH0, b0);
    if (tau == 0) {
      named_arrive(NB_H01, 256);
      mbar_wait(sb + BAR_FULL + 16, 0);
      g1_half<0>(acc[0], DLO_AH0 + 512, b1);
    }
    mbar_wait(sb + BAR_AFULL, 0);
    if (tau == 1) named_bar(NB_H2, 256);
    g1_half<1>(acc[1], DLO_AH1, b0);
    wg_commit();
    named_arrive_if(NB_H2, 256, tau == 0);
    if (tau) {
      mbar_wait(sb + BAR_FULL + (tau == 2 ? 168 : 24), 0);
      g1_half<0>(acc[0], DLO_AH0 + 512, b1);
      wg_commit();
      wg_wait<1>();
      mbar_arrive_elect(sb + BAR_EMPTY + 8 * st0);
    }
    mbar_wait(sb + BAR_AFULL + 8, 0);
    g1_half<0>(acc[1], DLO_AH1 + 512, b1);
    wg_commit();
    if (tau == 0) { wg_wait<1>(); mbar_arrive_elect(sb + BAR_EMPTY); }
  }
  if (tau < 2) {
    wg_wait<0>();
    mbar_arrive_elect(sb + BAR_EMPTY + 16 + 8 * tau);
#pragma unroll 1
    for (int kc = 2; kc < 7; kc++) {
      const int fill = 2 * kc + tau;
      mbar_wait2(sb + BAR_AFULL + 8 * kc, sb + BAR_FULL + 8 * fill);
      g1_issue(acc, kc, fill & 3);
      if (fill == 12) break;
      wg_wait<0>();
      mbar_arrive_elect(sb + BAR_EMPTY + 8 * (fill & 3));
    }
    if (tau) named_bar(NB_H01, 256);
  } else {
    g1_t2_step<2>(acc, hh, hbase, sb, rank, warp); g1_t2_step<3>(acc, hh, hbase, sb, rank, warp);
    g1_t2_step<4>(acc, hh, hbase, sb, rank, warp); g1_t2_step<5>(acc, hh, hbase, sb, rank, warp); g1_t2_step<6>(acc, hh, hbase, sb, rank, warp);
  }
  const int fb = tau == 2 ? 20 : 7 + 3 * tau;
#pragma unroll 1
  for (int kc = 7; kc < 9; kc++) {
    const int fill = fb + kc;
    mbar_wait2(sb + BAR_AFULL + 8 * kc, sb + BAR_FULL + 8 * fill);
    g1_issue(acc, kc, fill & 3);
    if (tau == 2 && kc == 7) hh_ready<1>(sb, rank, 1, warp);
    wg_wait<1>();
    mbar_arrive_elect(sb + BAR_EMPTY + 8 * ((fill == 14 ? 0 : fill - 1) & 3), fill != 17);
  }
  const uint64_t b9 = DLO_RING + (uint32_t)(((fb + 9) & 3) * 1024);
  const int slot = tau & 2;
  const uint32_t hb = hbase + slot * 16384;
  mbar_wait2(sb + (tau == 2 ? BAR_AFREE + 16 : BAR_AFULL + 72), sb + BAR_FULL + 8 * fb + 72);
  wg_fence();
  g1_half<0>(acc[0], DLO_AH0 + 9 * 512, b9);
  wg_commit();
  g1_half<0>(acc[1], DLO_AH1 + 9 * 512, b9);
  wg_commit();
  named_arrive(NB_H01 + wg, 256);
  wg_wait<2>();
  mbar_arrive_elect(sb + BAR_EMPTY + 8 * ((fb + 8) & 3));
  wg_wait<1>();
  g1_piece<0>(acc[0], hh, hb, tau == 2);
  wg_wait<0>();
  mbar_arrive_elect(sb + BAR_EMPTY + 8 * ((fb + 9) & 3));
  mbar_arrive_elect(sb + BAR_T2D, tau == 2);
  g1_piece<1>(acc[0], hh, hb, tau == 2); g1_piece<2>(acc[0], hh, hb, tau == 2);
  g1_piece<3>(acc[0], hh, hb, tau == 2);
  g1_piece<4>(acc[1], hh, hb, false);
  if (tau) {
    mbar_wait(sb + BAR_AFREE, 0);
    hh_store<0>(hh, hb, tau == 1); hh_store<1>(hh, hb, tau == 1); hh_store<2>(hh, hb, tau == 1); hh_store<3>(hh, hb, tau == 1);
    hh_ready<0>(sb, rank, slot, warp);
  }
  hh_store<4>(hh, hb, tau);
  g1_piece<5>(acc[1], hh, hb, tau); g1_piece<6>(acc[1], hh, hb, tau); g1_piece<7>(acc[1], hh, hb, tau);
  if (tau) hh_ready<1>(sb, rank, slot, warp);
}
template <int NT, bool FIRST> __device__ __forceinline__ void g2_step(float (*acc)[64], uint32_t sb, int fill, int i, int hand) {
  const uint64_t al = mkdesc(SB0, 8192, 1024, 1) + ((fill == 41 ? OFF_AH0 + 65536 : fill == 42 ? OFF_AH1 + 65536 : OFF_RING + ((fill > 42 ? fill - 2 : fill) & 3) * 16384) >> 4);
  const uint64_t b0 = DLO_AH0 + (uint32_t)(NT == 2 ? ((i & 1) ? (OFF_AH1 >> 4) : 0) + (i >> 1) * 1024 : i * 1024), b1 = NT == 2 ? b0 : b0 + (OFF_AH1 >> 4);
  if (NT == 2) mbar_wait2(sb + BAR_HFULL + 8 * i, sb + BAR_FULL + 8 * fill);
  else mbar_wait(sb + BAR_FULL + 8 * fill, 0);
  wg_fence();
  wgmma_ss<1, 0, FIRST ? 0 : 1>(acc[0], (al), (b0));
  wgmma_ss<1, 0, (FIRST && NT == 2) ? 0 : 1>(acc[NT - 1], (al + 512), (b1));
#pragma unroll
  for (int ks = 1; ks < 4; ks++) {
    wgmma_ss<1, 0, 1>(acc[0], (al + ks * 128), (b0 + ks * 2));
    wgmma_ss<1, 0, 1>(acc[NT - 1], (al + 512 + ks * 128), (b1 + ks * 2));
  }
  wg_commit();
  if (!FIRST) {
    named_arrive_if(hand, 256, i == 3 * NT - 1 && hand);
    wg_wait<1>();
    mbar_arrive_elect(sb + BAR_EMPTY + 8 * ((fill - 1) & 3), fill < 42);
  }
}
__host__ __device__ constexpr uint32_t stg_off(int v) { return v == 4 ? OFF_RING : v == 3 ? OFF_RING + 49152 : v == 1 ? OFF_AH1 + 49152 : OFF_AH0 + 49152; }
template <bool REL> __device__ __forceinline__ void g2_out(const float* acc, uint32_t sb, int v, int t) {
  const int lane = t & 31, warp = t >> 5;
  const uint32_t base = sb + stg_off(v) + (8 * (lane >> 4) + (lane & 7)) * 128 + (((2 * warp + ((lane >> 3) & 1)) ^ (lane & 7)) << 4);
#pragma unroll
  for (int c = 0; c < 16; c += 2) {
    uint32_t r[4];
#pragma unroll
    for (int i = 0; i < 4; i++) r[i] = pack_bf16(acc[4 * c + 2 * i], acc[4 * c + 2 * i + 1]);
    if (REL && c == 4) { wg_wait<0>(); mbar_arrive_elect(sb + BAR_EMPTY + 24); }
    if (c == 8) { fence_async_smem(); mbar_arrive_elect(sb + BAR_STG + 8 * v); }
    stsm4t(base + c * 1024, r);
  }
  fence_async_smem();
  mbar_arrive_elect(sb + BAR_STG2 + 8 * v);
}

template <int NT> __device__ __forceinline__ void g2_tile(float (*acc)[64], uint32_t sb, int fill0, int hand, int t) {
  g2_step<NT, true>(acc, sb, fill0, 0, hand);
#pragma unroll 1
  for (int i = 1; i < (NT == 2 ? 5 : 3); i++) g2_step<NT, false>(acc, sb, fill0 + i, i, hand);
  if (NT == 2) {
    const uint64_t al = DLO_RING + 3 * 1024, bl = DLO_AH1 + 2048;
    mbar_wait2(sb + BAR_HFULL + 40, sb + BAR_FULL + 8 * 35);
    wg_fence();
#pragma unroll
    for (int ks = 0; ks < 4; ks++) wgmma_ss<1, 0, 1>(acc[0], al + ks * 128, bl + ks * 2);
    wg_commit();
#pragma unroll
    for (int ks = 0; ks < 4; ks++) wgmma_ss<1, 0, 1>(acc[1], al + 512 + ks * 128, bl + ks * 2);
    wg_commit();
    named_arrive(hand, 256);
    wg_wait<2>();
    mbar_arrive_elect(sb + BAR_EMPTY + 16);
    wg_wait<1>();
    g2_out<true>(acc[0], sb, 0, t);
    return;
  }
  wg_wait<0>();
  mbar_arrive_elect(sb + BAR_EMPTY + 8 * ((fill0 + 3 * NT - 1) & 3), fill0 < 39);
}
__device__ __forceinline__ void mlp_role(uint32_t sb, const Ids& id) {
  const uint32_t rank = id.rank; const int wg = id.wg, t = id.t, lane = id.lane, warp = id.warp;
  float acc[2][64];
  uint32_t hh[32];
#pragma unroll
  for (int i = 0; i < 32; i++) asm volatile("" : "=r"(hh[i]));
  const uint32_t hbase = sb + OFF_AH0 + (16 * warp + (lane & 15)) * 128 + (((lane >> 4) ^ (lane & 7)) << 4);
#pragma unroll 1
  for (int tau = wg; tau < 3; tau += 2) {
    g1_tile(acc, hh, hbase, sb, rank, tau, wg, warp);
  }
  if (wg == 1) {
    named_bar(NB_H01, 256);
    g2_tile<2>(acc, sb, 30, NB_H10, t);
    g2_out<false>(acc[1], sb, 1, t);
  }
#pragma unroll 1
  for (int v = 2 + wg; v < 5; v += 2) {
    named_bar(NB_H10 - wg, 256);
    g2_tile<1>(acc, sb, 30 + 3 * v, v == 4 ? 0 : NB_H01 + wg, t);
    if (v < 4) asm volatile("barrier.cluster.arrive.relaxed.aligned;" ::: "memory");
    mbar_wait(sb + (v == 2 ? BAR_SFREE : v == 3 ? BAR_EMPTY + 24 : BAR_EMPTY), v == 3);
    g2_out<false>(acc[0], sb, v, t);
  }
}

__device__ __forceinline__ void l2_prefetch(const void* p, uint32_t bytes) { asm volatile("cp.async.bulk.prefetch.L2.global [%0], %1;" ::"l"(p), "r"(bytes) : "memory"); }

__device__ __forceinline__ void load_x(const Maps& tm, uint32_t sb, uint32_t rank, int rb, int c) {
  asm volatile("cp.async.bulk.tensor.5d.shared::cluster.global.mbarrier::complete_tx::bytes [%0], [%1, {%3, %3, %4, %3, %5}], [%2];" ::"r"(sb + OFF_AH0 + c * 8192),
               "l"(&tm.x), "r"(sb + BAR_X), "r"(0), "r"(8 * (int)rank), "r"(10 * rb + c) : "memory");
}
template <uint32_t PITCH> __device__ __forceinline__ void kv_loop(const Maps& tm, const Params& p, uint32_t sb, uint32_t rank, int rb, int c0, int w0, int warp, int lane, const uint4 sw) {
  constexpr uint32_t JP = 17 * PITCH, BOX = 136 * PITCH;
  const int pp = min(lane / 6, 4), rl = lane - pp * 6;
  const uint32_t wt[4] = {__byte_perm(sw.x, sw.z, 0x5410), __byte_perm(sw.x, sw.z, 0x7632), __byte_perm(sw.y, sw.w, 0x5410), __byte_perm(sw.y, sw.w, 0x7632)};
  const uint32_t ks0 = sb + OFF_AH1 - 16 * BOX + PITCH + (c0 - w0 + 2 * pp) * 2;
  uint32_t dst0[2], dmul[2];
#pragma unroll
  for (int e = 0; e < 2; e++) {
    const int ch = 2 * pp + e; const uint32_t dr = ch >= 5; const int lc = ch - 5 * dr;
    dst0[e] = sb + (dr == rank ? OFF_U + rank * U_SEG : OFF_AH0) + lc * U_CH;
    dmul[e] = dr == rank;
  }
  asm volatile("barrier.cluster.wait.aligned;" ::: "memory");
  int first = 4 * warp, nr = 4;
#pragma unroll 1
  for (int i = 0; first < 128; i++) {
    const int run = first + min(rl, nr - 1), box = run >> 4;
    const uint32_t ks = ks0 + run * PITCH + box * (2 * BOX - 16 * PITCH);
    const uint32_t o_own = (run & 15) * 16 + 2 * box * U_SEG, o_out = (run & 15) * 16 + box * U_SEG + (box < 4 ? 0 : OFF_OBOX - 4 * U_SEG - OFF_AH0);
    const int b0 = first >> 4, b1 = (first + nr - 1) >> 4, n0 = min(nr, 16 - (first & 15)), n1 = nr - n0;
    const bool send = (first & 15) + nr >= 16;
    mbar_wait2(sb + (i == 1 ? BAR_UOWN : BAR_KV + 8 * b0), sb + BAR_KV + 8 * b1);
    uint32_t kk[12], u[9];
#pragma unroll
    for (int j = 0; j < 4; j++) kk[j] = lds32(ks - PITCH + (4 + j) * JP);
    u[0] = lds32(ks + BOX - PITCH + 7 * JP);
#pragma unroll
    for (int j = 0; j < 8; j++) { kk[4 + j] = lds32(ks + j * JP); u[1 + j] = lds32(ks + BOX + j * JP); }
    nr = (i == 0 && warp == 2) ? 4 : 6;
    first = 24 * i + 14 + 6 * warp + ((i == 0 && warp < 3) ? 2 : 0);
#pragma unroll
    for (int j = 0; j < 9; j++) {
      uint32_t s = hmul2(kk[j], wt[3]);
      s = hfma2(kk[j + 1], wt[2], s); s = hfma2(kk[j + 2], wt[1], s); s = hfma2(kk[j + 3], wt[0], s);
      u[j] = hmul2(s, u[j]);
    }
#pragma unroll
    for (int e = 0; e < 2; e++) {
      const uint32_t sel = e ? 0x7632 : 0x5410, dst = dst0[e] + (dmul[e] ? o_own : o_out);
      sts128(dst, make_uint4(__byte_perm(u[1], u[0], sel), __byte_perm(u[3], u[2], sel), __byte_perm(u[5], u[4], sel), __byte_perm(u[7], u[6], sel)));
      sts128(dst + U_PAR, make_uint4(__byte_perm(u[2], u[1], sel), __byte_perm(u[4], u[3], sel), __byte_perm(u[6], u[5], sel), __byte_perm(u[8], u[7], sel)));
    }
    __syncwarp();
    asm volatile("{\n.reg .pred p, q;\nelect.sync _|p, 0xffffffff;\n@p mbarrier.arrive.shared::cta.b64 _, [%0], %2;\nsetp.ne.and.u32 q, %3, 0, p;\n@q mbarrier.arrive.shared::cta.b64 _, [%1], %3;\n}\n"
                 ::"r"(sb + BAR_UOWN + 8 * b0), "r"(sb + BAR_UOWN + 8 * b1), "r"(n0), "r"(n1) : "memory");
    if (send) {
      mbar_wait2(sb + BAR_UOWN + 8 * b0, sb + (b0 >= 2 ? BAR_U + 8 * (b0 - 2) : BAR_UOWN + 8 * b0));
      fence_async_smem();
      if (elect_one()) dsmem_copy(mapa(sb + OFF_U + (2 * b0 + rank) * U_SEG, rank ^ 1), sb + (b0 < 4 ? OFF_AH0 : OFF_OBOX - 4 * U_SEG) + b0 * U_SEG, U_SEG - 32, mapa(sb + BAR_U + 8 * b0, rank ^ 1));
      __syncwarp();
    }
    if (warp == 3) {
      if (elect_one()) {
        if (i < 2) { issue_kv(tm, sb, rank, PITCH == 64, w0, 2 * i + 4); issue_kv(tm, sb, rank, PITCH == 64, w0, 2 * i + 5); }
        if (i == 2) l2_prefetch((const char*)p.q + blockIdx.x * 20480, 20480);
        if (i == 3) l2_prefetch((const char*)p.w1 + blockIdx.x * 15360, 15360);
        if (i == 4) l2_prefetch((const char*)p.w3 + blockIdx.x * 15360, 15360);
      }
      __syncwarp();
    }
  }
}

__global__ void __cluster_dims__(2, 1, 1) __launch_bounds__(512, 1) fused_kernel(const __grid_constant__ Maps tm, const Params p) {
  extern __shared__ __align__(1024) uint8_t smem[];
  const uint32_t sb = smem_u32(smem);
  if (threadIdx.x < 160 && !(threadIdx.x & 32)) asm volatile("prefetch.global.L2 [%0];" ::"l"(p.f + (size_t)blockIdx.x * (5 * S_) + 64 * threadIdx.x));
  const int warp16 = __shfl_sync(0xffffffffu, threadIdx.x >> 5, 0), wg = warp16 >> 2;
  if (wg == 3) {
    asm volatile("setmaxnreg.dec.sync.aligned.u32 40;");
    const uint4 sw = __ldg(reinterpret_cast<const uint4*>(p.shift) + 5 * (blockIdx.x >> 1) + min((threadIdx.x & 31) / 6, 4));
    if ((warp16 & 3) == 0) {
      if (elect_one()) {
        const int c0 = 10 * (blockIdx.x >> 1), w0 = c0 & ~15;
        const bool wide = (c0 + 10 - w0) > 16;
        mbar_init(sb + BAR_KV, 1); mbar_init(sb + BAR_KV + 8, 1);
        asm volatile("fence.mbarrier_init.release.cluster;" ::: "memory");
        mbar_expect_tx(sb + BAR_KV, wide ? 17408 : 8704);
        issue_kv(tm, sb, blockIdx.x & 1, wide, w0, 0);
        mbar_expect_tx(sb + BAR_KV + 8, wide ? 17408 : 8704);
      }
      __syncwarp();
    }
    const Ids id = get_ids();
    const uint32_t rank = id.rank, cid = id.cid; const int lane = id.lane, warp = id.warp, rb = id.rb, quarter = id.quarter;
    const int c0 = 10 * cid, w0 = c0 & ~15;
    const bool wide = (c0 + 10 - w0) > 16;
    if (elect_one()) {
      if (warp == 1 || warp == 2) {
        const uint32_t b0 = sb + BAR_U + 32 * (warp - 1);
#pragma unroll
        for (int i = 0; i < 4; i++) { mbar_init(b0 + 8 * i, 1); mbar_init(b0 + (BAR_UOWN - BAR_U) + 8 * i, 16); }
        asm volatile("fence.mbarrier_init.release.cluster;" ::: "memory");
#pragma unroll
        for (int i = 0; i < 4; i++) mbar_expect_tx(b0 + 8 * i, U_SEG - 32);
      }
      if (warp == 3) {
        mbar_init(sb + BAR_ZREAD, 4); mbar_init(sb + BAR_ZREADE, 4); mbar_init(sb + BAR_X, 1);
#pragma unroll
        for (int i = 2; i < 8; i++) mbar_init(sb + BAR_KV + 8 * i, 1);
        asm volatile("fence.mbarrier_init.release.cluster;" ::: "memory");
        mbar_expect_tx(sb + BAR_X, 81920);
#pragma unroll
        for (int i = 2; i < 8; i++) mbar_expect_tx(sb + BAR_KV + 8 * i, wide ? 17408 : 8704);
        if ((c0 & 63) > 54) { issue_kv(tm, sb, rank, wide, w0, 2); issue_kv(tm, sb, rank, wide, w0, 3); }
      }
    }
    __syncwarp();
    asm volatile("barrier.cluster.arrive.relaxed.aligned;" ::: "memory");
    if (warp == 0) {
      if (elect_one()) { __nanosleep(1); issue_kv(tm, sb, rank, wide, w0, 1); }
      __syncwarp();
    }
    if (wide) kv_loop<64>(tm, p, sb, rank, rb, c0, w0, warp, lane, sw); else kv_loop<32>(tm, p, sb, rank, rb, c0, w0, warp, lane, sw);
    const int f0 = 384 * quarter, n0 = 320 * rank;
    const uint32_t adst = mapa(sb + OFF_AH1, rank ^ 1), abar = mapa(sb + BAR_AFULL, rank ^ 1);
    const uint32_t dsta = sb + OFF_RING + warp * 16384;
    if (warp == 3) {
      mbar_wait(sb + BAR_UOWN + 32, 0);
      if (elect_one()) {
#pragma unroll 1
        for (int c = 2; c < 10; c += 2) load_x(tm, sb, rank, rb, c);
      }
      __syncwarp();
    }
    if (warp == 2) {
      mbar_wait2(sb + BAR_U + 16, sb + BAR_U + 24);
      mbar_wait2(sb + BAR_U + 32, sb + BAR_U + 40);
      if (elect_one()) load_x(tm, sb, rank, rb, 0);
      __syncwarp();
    }
    if (warp == 3) {
      named_bar(NB_ZE, 384 + 32);
      if (elect_one()) global_arrive(&p.cnt[CNT_EARLY]);
      __syncwarp();
      named_bar(NB_INIT, 512);
      if (elect_one()) {
#pragma unroll 1
        for (int st = 0; st < 4; st++) {
          tma2d(sb + OFF_RING + st * 16384, &tm.w1, sb + BAR_FULL + 8 * st, f0 + 192 * rank + 64 * (st & 1), 32 * (st & 2));
          tma2d(sb + OFF_RING + st * 16384 + 8192, &tm.w3, sb + BAR_FULL + 8 * st, f0 + 192 * rank + 64 * (st & 1), 32 * (st & 2));
        }
      }
      __syncwarp();
    } else if (warp == 2) named_arrive(NB_INIT, 512);
    else named_bar(NB_INIT, 512);
    if (warp == 2) named_bar(NB_ZDONE, 384 + 32);
    if (elect_one()) {
      if (warp >= 2) {
        const int hf = 3 - warp;
        if (hf) { global_arrive(&p.cnt[CNT_LATE]); mbar_arrive(sb + BAR_CDONE); global_wait(&p.cnt[CNT_LATE], 128); }
        else { global_wait(&p.cnt[CNT_EARLY], 128); mbar_wait(sb + BAR_CDONE, 0); }
        asm volatile("fence.proxy.async.global;" ::: "memory");
#pragma unroll
        for (int kc = 0; kc < 2; kc++)
          asm volatile("cp.async.bulk.tensor.4d.shared::cluster.global.mbarrier::complete_tx::bytes [%0], [%1, {%3, %5, %5, %4}], [%2];" ::"r"(sb + OFF_AH1 + hf * 40960 + kc * 20480), "l"(&tm.z),
                       "r"(sb + BAR_ZFULL + 16 * hf + 8 * kc), "r"(2048 * hf + 128 * rb + 64 * (int)rank), "r"(5 * kc), "r"(0) : "memory");
      }
      if (warp == 1) {
        mbar_wait2(sb + BAR_ZREADE, sb + BAR_LNE);
        mbar_wait2(sb + BAR_ZFULL + 16, sb + BAR_ZFULL + 24);
#pragma unroll
        for (int c = 0; c < 5; c++) dsmem_copy(adst + c * 8192, sb + OFF_AH0 + c * 8192, 4096, abar + 8 * c);
      }
      if (warp == 3) {
        mbar_wait2(sb + BAR_ZREAD, sb + BAR_LN);
#pragma unroll
        for (int c = 0; c < 3; c++) dsmem_copy(adst + c * 8192 + 4096, sb + OFF_AH0 + c * 8192 + 4096, 4096, abar + 8 * c);
      }
#pragma unroll 1
      for (int fi = warp + 4; fi < 43; fi += 4) {
        const int fill = fi > 40 ? fi + 2 : fi;
        const uint32_t fb = sb + BAR_FULL + 8 * fill;
        const CUtensorMap *ta, *tb; int ca, cb, ra, rb2, cp = -1;
        if (fill < 30) {
          const int tau = fill < 14 ? fill & 1 : fill < 17 ? 0 : fill < 20 ? 1 : 2;
          const int kc = fill < 14 ? fill >> 1 : fill < 17 ? fill - 7 : fill < 20 ? fill - 10 : fill - 20;
          ta = &tm.w1; tb = &tm.w3; ca = cb = f0 + 192 * rank + 64 * tau; ra = rb2 = 64 * kc;
          if (fill < 16) cp = (int)((0x00A0980760540000ull >> (4 * fill)) & 15) - 1;
        } else if (fill < 36) {
          const int s = fill - 30;
          ta = tb = &tm.w2; ca = n0; cb = n0 + 64; ra = rb2 = f0 + 192 * ((s & 1) ^ rank) + (s < 4 ? 64 - 32 * (s & 2) : 128);
        } else {
          const int r = fill - 36, at = r / 3, i0 = r - 3 * at, i = i0 == 2 ? 2 : 1 - i0;
          ta = tb = &tm.w2; ca = cb = n0 + 128 + 64 * at; ra = f0 + 192 * rank + 64 * i; rb2 = f0 + 192 * (rank ^ 1) + 64 * i;
        }
        asm volatile("" : "+r"(ca), "+r"(cb), "+r"(ra), "+r"(rb2), "+r"(cp), "+l"(ta), "+l"(tb));
        mbar_wait(sb + BAR_EMPTY + 8 * warp, ((fi >> 2) - 1) & 1);
        tma2d(dsta, ta, fb, ca, ra);
        tma2d(dsta + 8192, tb, fb, cb, rb2);
        if (cp >= 0) {
          if (fill < 8) mbar_wait(sb + BAR_ZREAD, 0);
          const uint32_t o = cp * 8192 + (cp < 5 ? 4096 : 0);
          dsmem_copy(adst + o, sb + OFF_AH0 + o, cp < 5 ? 4096 : 8192, abar + 8 * cp);
        }
      }
    }
  } else if (wg == 2) {
    if ((sb & 0x3FFFF) != SB0) __trap();
    conv_role<1>(tm, p, sb);
    const Ids id = get_ids();
    ln_role<2>(p, sb, id);
    const uint32_t rank = id.rank; const int warp = id.warp, rb = id.rb;
    asm volatile("barrier.cluster.arrive.relaxed.aligned;" ::: "memory");
    if (warp == 0 && elect_one()) {
      global_arrive(&p.cnt[32 * (1 + rb)]);
      l2_prefetch((const char*)p.w2 + blockIdx.x * 15360, 15360);
      global_wait(&p.cnt[32 * (1 + rb)], 8);
      asm volatile("fence.proxy.async.global;" ::: "memory");
      const int c2 = 8 * (int)rank, c4 = 10 * rb + 5 * (int)rank;
      mbar_wait(sb + BAR_T2D, 0);
#pragma unroll
      for (int i = 0; i < 2; i++) {
        const uint32_t dst = sb + (i ? OFF_AH1 : OFF_AH0) + 65536, fb = sb + BAR_FULL + 8 * (41 + i);
        tma2d(dst, &tm.w2, fb, 320 * rank + 192 + 64 * i, 384 * id.quarter + 192 * rank + 128 - 64 * i);
        tma2d(dst + 8192, &tm.w2, fb, 320 * rank + 192 + 64 * i, 384 * id.quarter + 192 * (rank ^ 1) + 128 - 64 * i);
      }
#pragma unroll
      for (int v = 0; v < 5; v++) {
#pragma unroll
        for (int hf = 0; hf < 2; hf++) {
          mbar_wait(sb + (hf ? BAR_STG2 : BAR_STG) + 8 * v, 0);
          asm volatile("cp.reduce.async.bulk.tensor.5d.global.shared::cta.add.bulk_group [%0, {%2, %2, %3, %2, %4}], [%1];" ::"l"(&tm.out), "r"(sb + stg_off(v) + hf * 8192),
                       "r"(0), "r"(c2 ^ (8 * hf)), "r"(c4 + v) : "memory");
          if (v < 3) {
            asm volatile("cp.async.bulk.commit_group;" ::: "memory");
            asm volatile("cp.async.bulk.wait_group.read 1;" ::: "memory");
            if (2 * v + hf == 2) mbar_arrive(sb + BAR_SFREE);
          }
        }
      }
      asm volatile("cp.async.bulk.commit_group;" ::: "memory");
      asm volatile("cp.async.bulk.wait_group.read 0;" ::: "memory");
    }
    __syncwarp();
    asm volatile("barrier.cluster.wait.aligned;" ::: "memory");
  } else {
    conv_role<2>(tm, p, sb);
    const Ids id = get_ids();
    ln_role<4>(p, sb, id);
    mlp_role(sb, id);
    asm volatile("barrier.cluster.wait.aligned;" ::: "memory");
  }
}

typedef CUresult (*EncFn)(CUtensorMap*, CUtensorMapDataType, cuuint32_t, void*, const cuuint64_t*, const cuuint64_t*, const cuuint32_t*, const cuuint32_t*,
                          CUtensorMapInterleave, CUtensorMapSwizzle, CUtensorMapL2promotion, CUtensorMapFloatOOBfill);
static void make_map(EncFn enc, CUtensorMap* tm, const void* base, int rank, const cuuint64_t* gd, const cuuint64_t* gs, const cuuint32_t* bx, bool swz) {
  const cuuint32_t es[5] = {1, 1, 1, 1, 1};
  enc(tm, CU_TENSOR_MAP_DATA_TYPE_BFLOAT16, rank, (void*)base, gd, gs, bx, es, CU_TENSOR_MAP_INTERLEAVE_NONE, swz ? CU_TENSOR_MAP_SWIZZLE_128B : CU_TENSOR_MAP_SWIZZLE_NONE,
      CU_TENSOR_MAP_L2_PROMOTION_L2_128B, CU_TENSOR_MAP_FLOAT_OOB_FILL_NONE);
}

extern "C" void kernel_launch(void* const* d_in, const int* in_sizes, int n_in, void* d_out, int out_size) {
  Params p;
  p.q = (const bf16*)d_in[0]; p.shift = (const bf16*)d_in[3]; p.f = (const bf16*)d_in[4]; p.D = (const bf16*)d_in[5];
  p.w1 = (const bf16*)d_in[7]; p.w3 = (const bf16*)d_in[8]; p.w2 = (const bf16*)d_in[9]; p.out = (bf16*)d_out;
  void* fn = nullptr; cudaDriverEntryPointQueryResult qr;
  cudaGetDriverEntryPoint("cuTensorMapEncodeTiled", &fn, cudaEnableDefault, &qr);
  EncFn enc = (EncFn)fn;
  Maps m;
  {
    const cuuint64_t gd[3] = {640, 256, 8}, gs[2] = {8 * 1280, 1280}; const cuuint32_t b16[3] = {16, 17, 8}, b32[3] = {32, 17, 8};
    make_map(enc, &m.k16, d_in[1], 3, gd, gs, b16, false); make_map(enc, &m.k32, d_in[1], 3, gd, gs, b32, false);
    make_map(enc, &m.v16, d_in[2], 3, gd, gs, b16, false); make_map(enc, &m.v32, d_in[2], 3, gd, gs, b32, false);
  }
  {
    const cuuint64_t gd[5] = {64, 4, 16, 2, 160}, gs[4] = {256 * 1280, 16 * 1280, 1024 * 1280, 128}; const cuuint32_t bx[5] = {64, 4, 8, 2, 2}, bo[5] = {64, 4, 8, 2, 1};
    make_map(enc, &m.x, d_in[0], 5, gd, gs, bx, true); make_map(enc, &m.out, d_out, 5, gd, gs, bo, true);
  }
  {
    void* zp = nullptr; cudaGetSymbolAddress(&zp, g_z);
    void* cp = nullptr; cudaGetSymbolAddress(&cp, g_cnt);
    p.z = (uint4*)zp; p.cnt = (unsigned*)cp;
    const cuuint64_t gd[4] = {4096, 8, 4, 10}, gs[3] = {4 * 8192, 8192, 32 * 8192}; const cuuint32_t bx[4] = {64, 8, 4, 5};
    make_map(enc, &m.z, zp, 4, gd, gs, bx, true);
  }
  {
    const cuuint64_t g1[2] = {1536, 640}, s1[1] = {3072}, g2[2] = {640, 1536}, s2[1] = {1280}; const cuuint32_t bx[2] = {64, 64};
    make_map(enc, &m.w1, d_in[7], 2, g1, s1, bx, true); make_map(enc, &m.w3, d_in[8], 2, g1, s1, bx, true); make_map(enc, &m.w2, d_in[9], 2, g2, s2, bx, true);
  }
  cudaFuncSetAttribute(fused_kernel, cudaFuncAttributeMaxDynamicSharedMemorySize, SMEM_BYTES);
  fused_kernel<<<128, 512, SMEM_BYTES, cudaStreamPerThread>>>(m, p);
}
```
